```python
import torch

def _softmax(x, axis=-1):
    return torch.softmax(x, dim=axis)
def _gelu(x):
    return torch.nn.functional.gelu(x, approximate="tanh")
def _silu(x):
    return torch.nn.functional.silu(x)
def _sigmoid(x):
    return torch.sigmoid(x)
def _layernorm(x, axis=-1, eps=1e-5):
    m = x.mean(dim=axis, keepdim=True)
    v = x.var(dim=axis, keepdim=True, unbiased=False)
    return (x - m) / torch.sqrt(v + eps)
def _scatter_add(tgt, idx, src, axis=0):
    return tgt.clone().index_add_(axis, idx, src)
def _segment_sum(src, seg, n):
    out = torch.zeros((n,) + src.shape[1:], dtype=src.dtype)
    return out.index_add_(0, seg, src)
def _pad(x, pw):
    flat = tuple(v for pair in reversed(pw) for v in pair)
    return torch.nn.functional.pad(x, flat)

kernel_name = 'standalone__molecular_angular_gemnet__graph'

def setup_inputs():

    _w = (lambda a: (lambda t: t.to(torch.bfloat16) if t.is_floating_point() else t)(torch.as_tensor(a)))
    N, deg, De, L = 25000, 16, 16, 3
    E = N * deg
    T = E * deg
    NR = 8
    dist = torch.rand(E).to(float)
    angle = (torch.rand(T) * torch.pi).to(float)
    centers = torch.linspace(0.0, 1.0, NR).to(float)
    ang_freq = torch.arange(1, L + 1).to(float)
    return {
        "m": _w((lambda *s: torch.randn(*s, dtype=torch.bfloat16) * 0.05)(E, De)),
        "idx_in": _w((lambda lo, hi, *s: torch.randint(lo, hi, s))(0, E, T).to(torch.int64)),
        "idx_out": _w((lambda lo, hi, *s: torch.randint(lo, hi, s))(0, E, T).to(torch.int64)),
        "dist": _w(dist),
        "angle": _w(angle),
        "centers": _w(centers),
        "ang_freq": _w(ang_freq),
        "w_rbf": _w((lambda *s: torch.randn(*s, dtype=torch.bfloat16) * 0.2)(NR, De)),
        "w_sbf": _w((lambda *s: torch.randn(*s, dtype=torch.bfloat16) * 0.2)(NR * L, De)),
        "w_down": _w((lambda *s: torch.randn(*s, dtype=torch.bfloat16) * 0.2)(De, De)),
        "w_up": _w((lambda *s: torch.randn(*s, dtype=torch.bfloat16) * 0.2)(De, De)),
    }

def reference(m, idx_in, idx_out, dist, angle, centers, ang_freq, w_rbf, w_sbf, w_down, w_up):
    E, De = m.shape[0], m.shape[1]
    NR = centers.shape[0]
    L = ang_freq.shape[0]
    rbf = torch.exp(-10.0 * (dist[:, None] - centers[None, :]) ** 2)
    cbf = torch.cos(ang_freq[None, :] * angle[:, None])
    rbf_t = rbf[idx_out]
    sbf = torch.reshape(rbf_t[:, :, None] * cbf[:, None, :], (-1, NR * L))
    x = (m[idx_in] @ w_down) * (sbf @ w_sbf)
    agg = _segment_sum(x, idx_out, E)
    return m + (agg @ w_up) * (rbf @ w_rbf)
```

```cpp
#include <cuda_runtime.h>
#include <cuda_bf16.h>
#include <stdint.h>

namespace {

constexpr int DE = 16;
constexpr int NR = 8;
constexpr int NL = 3;

constexpr int NB_LOG = 8;
constexpr int NB = 1 << NB_LOG;
constexpr int MAX_E = 400000;
constexpr int MAX_BINS = (MAX_E + NB - 1) / NB;
constexpr int BINS_PAD = 2048;
constexpr int CAP = 4608;

constexpr int P_TILE = 6400;
constexpr int P_NT = 512;
constexpr int P_PER = 16;

constexpr int G_NT = 256;
constexpr int G_PER = CAP / G_NT;

__device__ uint2 g_records[(size_t)MAX_BINS * CAP];
__device__ int g_cursor[BINS_PAD];
__device__ float g_ovf[(size_t)MAX_BINS * NB * DE];

__device__ __forceinline__ float bf16r(float x) { return __bfloat162float(__float2bfloat16_rn(x)); }
__device__ __forceinline__ float bf16lo(uint32_t v) { return __uint_as_float(v << 16); }
__device__ __forceinline__ float bf16hi(uint32_t v) { return __uint_as_float(v & 0xffff0000u); }
__device__ __forceinline__ float ldbf(const __nv_bfloat16* p) { return __bfloat162float(*p); }

__device__ __noinline__ float cos_slow(float x) { return cosf(x); }

__device__ __forceinline__ float cbf_val(float f, float a) {
    float x = bf16r(f * a);
    float k = rintf(x * 0.15915494309189535f);
    float r = fmaf(k, -6.28318548202514648f, x);
    r = fmaf(k, 1.7484555e-7f, r);
    float c = __cosf(r);
    if (!(fabsf(x) < 32768.0f)) c = cos_slow(x);
    return bf16r(c);
}

__device__ __forceinline__ float rbf_val(float d, float c) {
    float t = bf16r(d - c);
    t = bf16r(t * t);
    t = bf16r(-10.0f * t);
    return bf16r(__expf(t));
}

__device__ __forceinline__ uint32_t pack_bf16(float lo, float hi) {
    __nv_bfloat162 v = __floats2bfloat162_rn(lo, hi);
    return *reinterpret_cast<uint32_t*>(&v);
}

__device__ __forceinline__ void mma16816(float* d, const uint32_t* a, const uint32_t* b) {
    asm volatile("mma.sync.aligned.m16n8k16.row.col.f32.bf16.bf16.f32 {%0,%1,%2,%3}, {%4,%5,%6,%7}, {%8,%9}, {%0,%1,%2,%3};"
                 : "+f"(d[0]), "+f"(d[1]), "+f"(d[2]), "+f"(d[3])
                 : "r"(a[0]), "r"(a[1]), "r"(a[2]), "r"(a[3]), "r"(b[0]), "r"(b[1]));
}
__device__ __forceinline__ void mma1688(float* d, const uint32_t* a, uint32_t b) {
    asm volatile("mma.sync.aligned.m16n8k8.row.col.f32.bf16.bf16.f32 {%0,%1,%2,%3}, {%4,%5}, {%6}, {%0,%1,%2,%3};"
                 : "+f"(d[0]), "+f"(d[1]), "+f"(d[2]), "+f"(d[3])
                 : "r"(a[0]), "r"(a[1]), "r"(b));
}

struct Params {
    const __nv_bfloat16* m;
    const int* idx_in;
    const int* idx_out;
    const __nv_bfloat16* dist;
    const __nv_bfloat16* angle;
    const __nv_bfloat16* centers;
    const __nv_bfloat16* ang_freq;
    const __nv_bfloat16* w_rbf;
    const __nv_bfloat16* w_sbf;
    const __nv_bfloat16* w_down;
    const __nv_bfloat16* w_up;
    __nv_bfloat16* out;
    int E, T, nbins;
};

__device__ __noinline__ void slow_triplet(const Params& p, int in, int out, float ang) {
    float mrow[DE], rb[NR], cb[NL];
    for (int k = 0; k < DE; k++) mrow[k] = ldbf(p.m + (size_t)in * DE + k);
    float d = ldbf(p.dist + out);
    for (int r = 0; r < NR; r++) rb[r] = rbf_val(d, ldbf(p.centers + r));
    for (int l = 0; l < NL; l++) cb[l] = cbf_val(ldbf(p.ang_freq + l), ang);
    for (int c = 0; c < DE; c++) {
        float md = 0.f, s = 0.f;
        for (int k = 0; k < DE; k++) md = fmaf(mrow[k], ldbf(p.w_down + k * DE + c), md);
        for (int r = 0; r < NR; r++)
            for (int l = 0; l < NL; l++) s = fmaf(rb[r] * cb[l], ldbf(p.w_sbf + (r * NL + l) * DE + c), s);
        atomicAdd(&g_ovf[(size_t)out * DE + c], md * s);
    }
}

__global__ void __launch_bounds__(P_NT) k_partition(const Params p) {
    extern __shared__ __align__(16) unsigned char smem_raw[];
    uint2* stage = reinterpret_cast<uint2*>(smem_raw);
    int* hist = reinterpret_cast<int*>(smem_raw + (size_t)P_TILE * 8);
    int* delta = hist + BINS_PAD;
    __shared__ int warp_sums[P_NT / 32];

    const int tid = threadIdx.x;
    const int lane = tid & 31, wid = tid >> 5;
    const int base = blockIdx.x * P_TILE;
    const int n = min(P_TILE, p.T - base);

    reinterpret_cast<int4*>(hist)[tid] = make_int4(0, 0, 0, 0);

    uint32_t rx[P_PER], ry[P_PER];
    int rank[P_PER];
#pragma unroll
    for (int v = 0; v < P_PER / 4; v++) {
        int i = (v * P_NT + tid) * 4;
        if (i + 3 < n) {
            int4 a = __ldcs(reinterpret_cast<const int4*>(p.idx_in + base + i));
            int4 b = __ldcs(reinterpret_cast<const int4*>(p.idx_out + base + i));
            uint2 c = __ldcs(reinterpret_cast<const uint2*>(p.angle + base + i));
            rx[v * 4 + 0] = (uint32_t)a.x | ((uint32_t)b.x << 24); ry[v * 4 + 0] = (c.x & 0xffffu) | (((uint32_t)b.x >> 8) << 16);
            rx[v * 4 + 1] = (uint32_t)a.y | ((uint32_t)b.y << 24); ry[v * 4 + 1] = (c.x >> 16) | (((uint32_t)b.y >> 8) << 16);
            rx[v * 4 + 2] = (uint32_t)a.z | ((uint32_t)b.z << 24); ry[v * 4 + 2] = (c.y & 0xffffu) | (((uint32_t)b.z >> 8) << 16);
            rx[v * 4 + 3] = (uint32_t)a.w | ((uint32_t)b.w << 24); ry[v * 4 + 3] = (c.y >> 16) | (((uint32_t)b.w >> 8) << 16);
        } else {
#pragma unroll
            for (int u = 0; u < 4; u++) {
                if (i + u < n) {
                    uint32_t a = (uint32_t)p.idx_in[base + i + u];
                    uint32_t b = (uint32_t)p.idx_out[base + i + u];
                    uint32_t c = (uint32_t)(reinterpret_cast<const unsigned short*>(p.angle)[base + i + u]);
                    rx[v * 4 + u] = a | (b << 24); ry[v * 4 + u] = c | ((b >> 8) << 16);
                } else {
                    rx[v * 4 + u] = 0; ry[v * 4 + u] = 0xffffffffu;
                }
            }
        }
    }
    __syncthreads();
#pragma unroll
    for (int j = 0; j < P_PER; j++) {
        if (ry[j] != 0xffffffffu) rank[j] = atomicAdd(&hist[ry[j] >> 16], 1);
    }
    __syncthreads();
    int4 c4 = reinterpret_cast<int4*>(hist)[tid];
    int g0 = 0, g1 = 0, g2 = 0, g3 = 0;
    if (c4.x) g0 = atomicAdd(&g_cursor[tid * 4 + 0], c4.x);
    if (c4.y) g1 = atomicAdd(&g_cursor[tid * 4 + 1], c4.y);
    if (c4.z) g2 = atomicAdd(&g_cursor[tid * 4 + 2], c4.z);
    if (c4.w) g3 = atomicAdd(&g_cursor[tid * 4 + 3], c4.w);
    int s = c4.x + c4.y + c4.z + c4.w;
    int inc = s;
#pragma unroll
    for (int o = 1; o < 32; o <<= 1) {
        int t = __shfl_up_sync(0xffffffffu, inc, o);
        if (lane >= o) inc += t;
    }
    if (lane == 31) warp_sums[wid] = inc;
    __syncthreads();
    int woff = 0;
    {
        int ws = (lane < P_NT / 32) ? warp_sums[lane] : 0;
        int winc = ws;
#pragma unroll
        for (int o = 1; o < 32; o <<= 1) {
            int t = __shfl_up_sync(0xffffffffu, winc, o);
            if (lane >= o) winc += t;
        }
        woff = __shfl_sync(0xffffffffu, winc - ws, wid);
    }
    int e0 = woff + inc - s;
    int e1 = e0 + c4.x, e2 = e1 + c4.y, e3 = e2 + c4.z;
    reinterpret_cast<int4*>(hist)[tid] = make_int4(e0, e1, e2, e3);
    reinterpret_cast<int4*>(delta)[tid] = make_int4(g0 - e0, g1 - e1, g2 - e2, g3 - e3);
    __syncthreads();
#pragma unroll
    for (int j = 0; j < P_PER; j++) {
        if (ry[j] != 0xffffffffu) {
            int pos = hist[ry[j] >> 16] + rank[j];
            stage[pos] = make_uint2(rx[j], ry[j]);
        }
    }
    __syncthreads();
    for (int i = tid; i < n; i += P_NT) {
        uint2 r = stage[i];
        int bin = r.y >> 16;
        int d = i + delta[bin];
        if (d < CAP) {
            g_records[(size_t)bin * CAP + d] = r;
        } else {
            slow_triplet(p, (int)(r.x & 0xffffffu), (bin << NB_LOG) | (int)(r.x >> 24), bf16lo(r.y & 0xffffu));
        }
    }
}

__global__ void __launch_bounds__(G_NT) k_gather(const Params p) {
    extern __shared__ __align__(16) unsigned char smem_raw[];
    float4* srec = reinterpret_cast<float4*>(smem_raw);
    __shared__ int cnts[NB];
    __shared__ int start[NB + 1];
    __shared__ int warp_sums[G_NT / 32];

    const int tid = threadIdx.x;
    const int lane = tid & 31, wid = tid >> 5;
    const int bin = blockIdx.x;
    const int total = g_cursor[bin];
    const int n = min(total, CAP);
    const bool ovf = total > CAP;

    cnts[tid] = 0;
    const uint2* rec = g_records + (size_t)bin * CAP;
    uint2 r[G_PER];
#pragma unroll
    for (int j = 0; j < G_PER; j++) {
        int i = j * G_NT + tid;
        if (i < n) r[j] = __ldcs(rec + i);
    }
    const float f0 = ldbf(p.ang_freq + 0), f1 = ldbf(p.ang_freq + 1), f2 = ldbf(p.ang_freq + 2);
    __syncthreads();
    if (tid == 0) g_cursor[bin] = 0;
    int rank[G_PER];
#pragma unroll
    for (int j = 0; j < G_PER; j++) {
        int i = j * G_NT + tid;
        if (i < n) rank[j] = atomicAdd(&cnts[r[j].x >> 24], 1);
    }
    __syncthreads();
    {
        int c = cnts[tid];
        int inc = c;
#pragma unroll
        for (int o = 1; o < 32; o <<= 1) {
            int t = __shfl_up_sync(0xffffffffu, inc, o);
            if (lane >= o) inc += t;
        }
        if (lane == 31) warp_sums[wid] = inc;
        __syncthreads();
        int woff = 0;
#pragma unroll
        for (int w = 0; w < G_NT / 32; w++) woff += (w < wid) ? warp_sums[w] : 0;
        start[tid] = woff + inc - c;
        if (tid == G_NT - 1) start[NB] = woff + inc;
    }
    __syncthreads();
#pragma unroll
    for (int j = 0; j < G_PER; j++) {
        int i = j * G_NT + tid;
        if (i < n) {
            float a = bf16lo(r[j].y & 0xffffu);
            float4 o;
            o.x = __uint_as_float(r[j].x & 0xffffffu);
            o.y = cbf_val(f0, a);
            o.z = cbf_val(f1, a);
            o.w = cbf_val(f2, a);
            srec[start[r[j].x >> 24] + rank[j]] = o;
        }
    }
    __syncthreads();

    const int g = lane >> 2, q = lane & 3;
    uint32_t bdown[2][2], bup[2][2], bsbf[NL][2], brbf[2];
#pragma unroll
    for (int j = 0; j < 2; j++) {
        int oc = 4 * (g >> 1) + 2 * j + (g & 1);
        const unsigned short* wd = reinterpret_cast<const unsigned short*>(p.w_down);
        const unsigned short* wu = reinterpret_cast<const unsigned short*>(p.w_up);
        const unsigned short* ws = reinterpret_cast<const unsigned short*>(p.w_sbf);
        const unsigned short* wr = reinterpret_cast<const unsigned short*>(p.w_rbf);
        bdown[j][0] = (uint32_t)wd[(4 * q + 0) * DE + oc] | ((uint32_t)wd[(4 * q + 1) * DE + oc] << 16);
        bdown[j][1] = (uint32_t)wd[(4 * q + 2) * DE + oc] | ((uint32_t)wd[(4 * q + 3) * DE + oc] << 16);
        bup[j][0] = (uint32_t)wu[(4 * q + 0) * DE + oc] | ((uint32_t)wu[(4 * q + 1) * DE + oc] << 16);
        bup[j][1] = (uint32_t)wu[(4 * q + 2) * DE + oc] | ((uint32_t)wu[(4 * q + 3) * DE + oc] << 16);
#pragma unroll
        for (int l = 0; l < NL; l++)
            bsbf[l][j] = (uint32_t)ws[((2 * q) * NL + l) * DE + oc] | ((uint32_t)ws[((2 * q + 1) * NL + l) * DE + oc] << 16);
        brbf[j] = (uint32_t)wr[(2 * q) * DE + oc] | ((uint32_t)wr[(2 * q + 1) * DE + oc] << 16);
    }
    const float cen0 = ldbf(p.centers + 2 * q), cen1 = ldbf(p.centers + 2 * q + 1);
    const uint2* m8 = reinterpret_cast<const uint2*>(p.m);

    constexpr int GROUPS = NB / 16 / (G_NT / 32);
#pragma unroll 1
    for (int grp = 0; grp < GROUPS; grp++) {
        const int le0 = (wid * GROUPS + grp) * 16;
        float acc[2][NL][4];
#pragma unroll
        for (int h = 0; h < 2; h++) {
#pragma unroll
            for (int l = 0; l < NL; l++)
#pragma unroll
                for (int c = 0; c < 4; c++) acc[h][l][c] = 0.f;
            const int le = le0 + g + 8 * h;
            const int s = start[le], e = start[le + 1];
            for (int i = s; i < e; i += 4) {
                float4 rr[4];
                uint2 v[4];
#pragma unroll
                for (int u = 0; u < 4; u++) {
                    if (i + u < e) {
                        rr[u] = srec[i + u];
                        v[u] = __ldg(m8 + (size_t)__float_as_uint(rr[u].x) * 4 + q);
                    } else {
                        rr[u] = make_float4(0.f, 0.f, 0.f, 0.f);
                        v[u] = make_uint2(0u, 0u);
                    }
                }
#pragma unroll
                for (int u = 0; u < 4; u++) {
                    float x0 = bf16lo(v[u].x), x1 = bf16hi(v[u].x), x2 = bf16lo(v[u].y), x3 = bf16hi(v[u].y);
                    acc[h][0][0] = fmaf(rr[u].y, x0, acc[h][0][0]);
                    acc[h][0][1] = fmaf(rr[u].y, x1, acc[h][0][1]);
                    acc[h][0][2] = fmaf(rr[u].y, x2, acc[h][0][2]);
                    acc[h][0][3] = fmaf(rr[u].y, x3, acc[h][0][3]);
                    acc[h][1][0] = fmaf(rr[u].z, x0, acc[h][1][0]);
                    acc[h][1][1] = fmaf(rr[u].z, x1, acc[h][1][1]);
                    acc[h][1][2] = fmaf(rr[u].z, x2, acc[h][1][2]);
                    acc[h][1][3] = fmaf(rr[u].z, x3, acc[h][1][3]);
                    acc[h][2][0] = fmaf(rr[u].w, x0, acc[h][2][0]);
                    acc[h][2][1] = fmaf(rr[u].w, x1, acc[h][2][1]);
                    acc[h][2][2] = fmaf(rr[u].w, x2, acc[h][2][2]);
                    acc[h][2][3] = fmaf(rr[u].w, x3, acc[h][2][3]);
                }
            }
        }
        const int eA = bin * NB + le0 + g, eB = eA + 8;
        const bool vA = eA < p.E, vB = eB < p.E;
        float dA = vA ? ldbf(p.dist + eA) : 0.f;
        float dB = vB ? ldbf(p.dist + eB) : 0.f;
        uint2 mA = vA ? __ldg(m8 + (size_t)eA * 4 + q) : make_uint2(0u, 0u);
        uint2 mB = vB ? __ldg(m8 + (size_t)eB * 4 + q) : make_uint2(0u, 0u);
        uint32_t arbf[2];
        arbf[0] = pack_bf16(rbf_val(dA, cen0), rbf_val(dA, cen1));
        arbf[1] = pack_bf16(rbf_val(dB, cen0), rbf_val(dB, cen1));
        float agg[2][4];
#pragma unroll
        for (int j = 0; j < 2; j++)
#pragma unroll
            for (int c = 0; c < 4; c++) agg[j][c] = 0.f;
#pragma unroll
        for (int l = 0; l < NL; l++) {
            uint32_t ahi[4], alo[4];
            ahi[0] = pack_bf16(acc[0][l][0], acc[0][l][1]);
            ahi[1] = pack_bf16(acc[1][l][0], acc[1][l][1]);
            ahi[2] = pack_bf16(acc[0][l][2], acc[0][l][3]);
            ahi[3] = pack_bf16(acc[1][l][2], acc[1][l][3]);
            alo[0] = pack_bf16(acc[0][l][0] - bf16lo(ahi[0]), acc[0][l][1] - bf16hi(ahi[0]));
            alo[1] = pack_bf16(acc[1][l][0] - bf16lo(ahi[1]), acc[1][l][1] - bf16hi(ahi[1]));
            alo[2] = pack_bf16(acc[0][l][2] - bf16lo(ahi[2]), acc[0][l][3] - bf16hi(ahi[2]));
            alo[3] = pack_bf16(acc[1][l][2] - bf16lo(ahi[3]), acc[1][l][3] - bf16hi(ahi[3]));
#pragma unroll
            for (int j = 0; j < 2; j++) {
                float S[4] = {0.f, 0.f, 0.f, 0.f};
                float G[4] = {0.f, 0.f, 0.f, 0.f};
                mma16816(S, alo, bdown[j]);
                mma16816(S, ahi, bdown[j]);
                mma1688(G, arbf, bsbf[l][j]);
#pragma unroll
                for (int c = 0; c < 4; c++) agg[j][c] = fmaf(S[c], G[c], agg[j][c]);
            }
        }
        if (ovf) {
            if (vA) {
                float4* pa = reinterpret_cast<float4*>(g_ovf + (size_t)eA * DE + 4 * q);
                float4 o = *pa; *pa = make_float4(0.f, 0.f, 0.f, 0.f);
                agg[0][0] += o.x; agg[0][1] += o.y; agg[1][0] += o.z; agg[1][1] += o.w;
            }
            if (vB) {
                float4* pb = reinterpret_cast<float4*>(g_ovf + (size_t)eB * DE + 4 * q);
                float4 o = *pb; *pb = make_float4(0.f, 0.f, 0.f, 0.f);
                agg[0][2] += o.x; agg[0][3] += o.y; agg[1][2] += o.z; agg[1][3] += o.w;
            }
        }
        {
            uint32_t ahi[4], alo[4];
            ahi[0] = pack_bf16(agg[0][0], agg[0][1]);
            ahi[1] = pack_bf16(agg[0][2], agg[0][3]);
            ahi[2] = pack_bf16(agg[1][0], agg[1][1]);
            ahi[3] = pack_bf16(agg[1][2], agg[1][3]);
            alo[0] = pack_bf16(agg[0][0] - bf16lo(ahi[0]), agg[0][1] - bf16hi(ahi[0]));
            alo[1] = pack_bf16(agg[0][2] - bf16lo(ahi[1]), agg[0][3] - bf16hi(ahi[1]));
            alo[2] = pack_bf16(agg[1][0] - bf16lo(ahi[2]), agg[1][1] - bf16hi(ahi[2]));
            alo[3] = pack_bf16(agg[1][2] - bf16lo(ahi[3]), agg[1][3] - bf16hi(ahi[3]));
            float res[2][4];
#pragma unroll
            for (int j = 0; j < 2; j++) {
                float U[4] = {0.f, 0.f, 0.f, 0.f};
                float R[4] = {0.f, 0.f, 0.f, 0.f};
                mma16816(U, alo, bup[j]);
                mma16816(U, ahi, bup[j]);
                mma1688(R, arbf, brbf[j]);
#pragma unroll
                for (int c = 0; c < 4; c++) res[j][c] = U[c] * R[c];
            }
            uint2 oA, oB;
            oA.x = pack_bf16(bf16lo(mA.x) + res[0][0], bf16hi(mA.x) + res[0][1]);
            oA.y = pack_bf16(bf16lo(mA.y) + res[1][0], bf16hi(mA.y) + res[1][1]);
            oB.x = pack_bf16(bf16lo(mB.x) + res[0][2], bf16hi(mB.x) + res[0][3]);
            oB.y = pack_bf16(bf16lo(mB.y) + res[1][2], bf16hi(mB.y) + res[1][3]);
            uint2* o8 = reinterpret_cast<uint2*>(p.out);
            if (vA) o8[(size_t)eA * 4 + q] = oA;
            if (vB) o8[(size_t)eB * 4 + q] = oB;
        }
    }
}

}

extern "C" void kernel_launch(void* const* d_in, const int* in_sizes, int n_in,
                              void* d_out, int out_size) {
    Params p;
    p.m = (const __nv_bfloat16*)d_in[0];
    p.idx_in = (const int*)d_in[1];
    p.idx_out = (const int*)d_in[2];
    p.dist = (const __nv_bfloat16*)d_in[3];
    p.angle = (const __nv_bfloat16*)d_in[4];
    p.centers = (const __nv_bfloat16*)d_in[5];
    p.ang_freq = (const __nv_bfloat16*)d_in[6];
    p.w_rbf = (const __nv_bfloat16*)d_in[7];
    p.w_sbf = (const __nv_bfloat16*)d_in[8];
    p.w_down = (const __nv_bfloat16*)d_in[9];
    p.w_up = (const __nv_bfloat16*)d_in[10];
    p.out = (__nv_bfloat16*)d_out;
    p.E = in_sizes[3];
    p.T = in_sizes[1];
    p.nbins = (p.E + NB - 1) / NB;

    const int smem1 = P_TILE * 8 + 2 * BINS_PAD * 4;
    const int smem2 = CAP * 16;
    static bool init = false;
    if (!init) {
        cudaFuncSetAttribute(k_partition, cudaFuncAttributeMaxDynamicSharedMemorySize, smem1);
        cudaFuncSetAttribute(k_gather, cudaFuncAttributeMaxDynamicSharedMemorySize, smem2);
        init = true;
    }
    int ntiles = (p.T + P_TILE - 1) / P_TILE;
    k_partition<<<ntiles, P_NT, smem1>>>(p);
    k_gather<<<p.nbins, G_NT, smem2>>>(p);
}
```

```cpp
#include <cuda_runtime.h>
#include <cuda_bf16.h>
#include <stdint.h>

namespace {

constexpr int DE = 16;
constexpr int NR = 8;
constexpr int NL = 3;

constexpr int NB_LOG = 9;
constexpr int NB = 1 << NB_LOG;
constexpr int IDX_BITS = 32 - NB_LOG;
constexpr uint32_t IDX_MASK = (1u << IDX_BITS) - 1u;
constexpr int MAX_E = 400000;
constexpr int MAX_BINS = (MAX_E + NB - 1) / NB;
constexpr int BINS_PAD = 1024;
constexpr int CAP = 8960;

constexpr int P_TILE = 8192;
constexpr int P_NT = 512;
constexpr int P_PER = P_TILE / P_NT;

constexpr int G_NT = 512;
constexpr int G_PER = (CAP + G_NT - 1) / G_NT;
constexpr int NGRP = NB / 8;
constexpr int CAPS = CAP + NGRP * 16;

__device__ uint2 g_records[(size_t)MAX_BINS * CAP];
__device__ int g_cursor[BINS_PAD];
__device__ float g_ovf[(size_t)MAX_BINS * NB * DE];

__device__ __forceinline__ float bf16r(float x) { return __bfloat162float(__float2bfloat16_rn(x)); }
__device__ __forceinline__ float bf16lo(uint32_t v) { return __uint_as_float(v << 16); }
__device__ __forceinline__ float bf16hi(uint32_t v) { return __uint_as_float(v & 0xffff0000u); }
__device__ __forceinline__ float ldbf(const __nv_bfloat16* p) { return __bfloat162float(*p); }

__device__ __noinline__ float cos_slow(float x) { return cosf(x); }

__device__ __forceinline__ float cos_any(float x) {
    float c = __cosf(x);
    if (!(fabsf(x) < 256.0f)) c = cos_slow(x);
    return c;
}

__device__ __forceinline__ float rbf_val(float d, float c) {
    float t = bf16r(d - c);
    t = bf16r(t * t);
    t = bf16r(-10.0f * t);
    return __expf(t);
}

__device__ __forceinline__ uint32_t pack_bf16(float lo, float hi) {
    __nv_bfloat162 v = __floats2bfloat162_rn(lo, hi);
    return *reinterpret_cast<uint32_t*>(&v);
}
__device__ __forceinline__ uint32_t mul_bf16x2(uint32_t a, uint32_t b) {
    __nv_bfloat162 r = __hmul2(*reinterpret_cast<__nv_bfloat162*>(&a), *reinterpret_cast<__nv_bfloat162*>(&b));
    return *reinterpret_cast<uint32_t*>(&r);
}
__device__ __forceinline__ uint32_t cos_bf16x2(uint32_t x) {
    return pack_bf16(cos_any(bf16lo(x)), cos_any(bf16hi(x)));
}

__device__ __forceinline__ void mma16816(float* d, const uint32_t* a, uint32_t b0, uint32_t b1) {
    asm volatile("mma.sync.aligned.m16n8k16.row.col.f32.bf16.bf16.f32 {%0,%1,%2,%3}, {%4,%5,%6,%7}, {%8,%9}, {%0,%1,%2,%3};"
                 : "+f"(d[0]), "+f"(d[1]), "+f"(d[2]), "+f"(d[3])
                 : "r"(a[0]), "r"(a[1]), "r"(a[2]), "r"(a[3]), "r"(b0), "r"(b1));
}
__device__ __forceinline__ void mma1688(float* d, const uint32_t* a, uint32_t b) {
    asm volatile("mma.sync.aligned.m16n8k8.row.col.f32.bf16.bf16.f32 {%0,%1,%2,%3}, {%4,%5}, {%6}, {%0,%1,%2,%3};"
                 : "+f"(d[0]), "+f"(d[1]), "+f"(d[2]), "+f"(d[3])
                 : "r"(a[0]), "r"(a[1]), "r"(b));
}
__device__ __forceinline__ uint32_t movm(uint32_t a) {
    uint32_t d;
    asm volatile("movmatrix.sync.aligned.m8n8.trans.b16 %0, %1;" : "=r"(d) : "r"(a));
    return d;
}
__device__ __forceinline__ uint32_t prmt(uint32_t a, uint32_t b, uint32_t sel) {
    uint32_t d;
    asm("prmt.b32 %0, %1, %2, %3;" : "=r"(d) : "r"(a), "r"(b), "r"(sel));
    return d;
}

struct Params {
    const __nv_bfloat16* m;
    const int* idx_in;
    const int* idx_out;
    const __nv_bfloat16* dist;
    const __nv_bfloat16* angle;
    const __nv_bfloat16* centers;
    const __nv_bfloat16* ang_freq;
    const __nv_bfloat16* w_rbf;
    const __nv_bfloat16* w_sbf;
    const __nv_bfloat16* w_down;
    const __nv_bfloat16* w_up;
    __nv_bfloat16* out;
    int E, T, nbins;
};

__device__ __noinline__ void slow_triplet(const Params* pp, int in, int out, float ang) {
    const Params& p = *pp;
    float mrow[DE], rb[NR], cb[NL];
    for (int k = 0; k < DE; k++) mrow[k] = ldbf(p.m + (size_t)in * DE + k);
    float d = ldbf(p.dist + out);
    for (int r = 0; r < NR; r++) rb[r] = bf16r(rbf_val(d, ldbf(p.centers + r)));
    for (int l = 0; l < NL; l++) cb[l] = bf16r(cos_any(bf16r(ldbf(p.ang_freq + l) * ang)));
    for (int c = 0; c < DE; c++) {
        float md = 0.f, s = 0.f;
        for (int k = 0; k < DE; k++) md = fmaf(mrow[k], ldbf(p.w_down + k * DE + c), md);
        for (int r = 0; r < NR; r++)
            for (int l = 0; l < NL; l++) s = fmaf(rb[r] * cb[l], ldbf(p.w_sbf + (r * NL + l) * DE + c), s);
        atomicAdd(&g_ovf[(size_t)out * DE + c], md * s);
    }
}

__global__ void __launch_bounds__(P_NT, 2) k_partition(const __grid_constant__ Params p) {
    extern __shared__ __align__(16) unsigned char smem_raw[];
    uint2* stage = reinterpret_cast<uint2*>(smem_raw);
    int* hist = reinterpret_cast<int*>(smem_raw + (size_t)P_TILE * 8);
    int* delta = hist + BINS_PAD;
    __shared__ int warp_sums[P_NT / 32];
    constexpr int BPT = BINS_PAD / P_NT;
    static_assert(BPT == 2, "scan written for 2 bins per thread");

    const int tid = threadIdx.x;
    const int lane = tid & 31, wid = tid >> 5;
    const int base = blockIdx.x * P_TILE;
    const int n = min(P_TILE, p.T - base);

    reinterpret_cast<int2*>(hist)[tid] = make_int2(0, 0);

    uint32_t rx[P_PER], ry[P_PER];
    int rank[P_PER];
    if (n == P_TILE) {
#pragma unroll
        for (int v = 0; v < P_PER / 4; v++) {
            int i = (v * P_NT + tid) * 4;
            int4 a = __ldcs(reinterpret_cast<const int4*>(p.idx_in + base + i));
            int4 b = __ldcs(reinterpret_cast<const int4*>(p.idx_out + base + i));
            uint2 c = __ldcs(reinterpret_cast<const uint2*>(p.angle + base + i));
            rx[v * 4 + 0] = (uint32_t)a.x | ((uint32_t)b.x << IDX_BITS); ry[v * 4 + 0] = (c.x & 0xffffu) | (((uint32_t)b.x >> NB_LOG) << 16);
            rx[v * 4 + 1] = (uint32_t)a.y | ((uint32_t)b.y << IDX_BITS); ry[v * 4 + 1] = (c.x >> 16) | (((uint32_t)b.y >> NB_LOG) << 16);
            rx[v * 4 + 2] = (uint32_t)a.z | ((uint32_t)b.z << IDX_BITS); ry[v * 4 + 2] = (c.y & 0xffffu) | (((uint32_t)b.z >> NB_LOG) << 16);
            rx[v * 4 + 3] = (uint32_t)a.w | ((uint32_t)b.w << IDX_BITS); ry[v * 4 + 3] = (c.y >> 16) | (((uint32_t)b.w >> NB_LOG) << 16);
        }
    } else {
#pragma unroll
        for (int j = 0; j < P_PER; j++) {
            int i = ((j >> 2) * P_NT + tid) * 4 + (j & 3);
            if (i < n) {
                uint32_t a = (uint32_t)p.idx_in[base + i];
                uint32_t b = (uint32_t)p.idx_out[base + i];
                uint32_t c = (uint32_t)(reinterpret_cast<const unsigned short*>(p.angle)[base + i]);
                rx[j] = a | (b << IDX_BITS); ry[j] = c | ((b >> NB_LOG) << 16);
            } else {
                rx[j] = 0; ry[j] = 0xffffffffu;
            }
        }
    }
    __syncthreads();
#pragma unroll
    for (int j = 0; j < P_PER; j++) {
        if (ry[j] != 0xffffffffu) rank[j] = atomicAdd(&hist[ry[j] >> 16], 1);
    }
    __syncthreads();
    int2 c2 = reinterpret_cast<int2*>(hist)[tid];
    int g0 = 0, g1 = 0;
    if (c2.x) g0 = atomicAdd(&g_cursor[tid * 2 + 0], c2.x);
    if (c2.y) g1 = atomicAdd(&g_cursor[tid * 2 + 1], c2.y);
    int s = c2.x + c2.y;
    int inc = s;
#pragma unroll
    for (int o = 1; o < 32; o <<= 1) {
        int t = __shfl_up_sync(0xffffffffu, inc, o);
        if (lane >= o) inc += t;
    }
    if (lane == 31) warp_sums[wid] = inc;
    __syncthreads();
    int woff = 0;
    {
        int ws = (lane < P_NT / 32) ? warp_sums[lane] : 0;
        int winc = ws;
#pragma unroll
        for (int o = 1; o < 32; o <<= 1) {
            int t = __shfl_up_sync(0xffffffffu, winc, o);
            if (lane >= o) winc += t;
        }
        woff = __shfl_sync(0xffffffffu, winc - ws, wid);
    }
    int e0 = woff + inc - s;
    int e1 = e0 + c2.x;
    reinterpret_cast<int2*>(hist)[tid] = make_int2(e0, e1);
    __syncthreads();
#pragma unroll
    for (int j = 0; j < P_PER; j++) {
        if (ry[j] != 0xffffffffu) {
            int pos = hist[ry[j] >> 16] + rank[j];
            stage[pos] = make_uint2(rx[j], ry[j]);
        }
    }
    reinterpret_cast<int2*>(delta)[tid] = make_int2(g0 - e0, g1 - e1);
    __syncthreads();
#pragma unroll 4
    for (int i = tid; i < n; i += P_NT) {
        uint2 r = stage[i];
        int bin = r.y >> 16;
        int d = i + delta[bin];
        if (d < CAP) {
            g_records[(size_t)bin * CAP + d] = r;
        } else {
            slow_triplet(&p, (int)(r.x & IDX_MASK), (bin << NB_LOG) | (int)(r.x >> IDX_BITS), bf16lo(r.y & 0xffffu));
        }
    }
}

__global__ void __launch_bounds__(G_NT, 2) k_gather(const __grid_constant__ Params p) {
    extern __shared__ __align__(16) unsigned char smem_raw[];
    uint32_t* sidx = reinterpret_cast<uint32_t*>(smem_raw);
    uint4* sc01 = reinterpret_cast<uint4*>(smem_raw + (size_t)CAPS * 4);
    unsigned short* sc2 = reinterpret_cast<unsigned short*>(smem_raw + (size_t)CAPS * 8);
    __shared__ int cnts[NGRP];
    __shared__ int gstart[NGRP + 1];

    const int tid = threadIdx.x;
    const int lane = tid & 31, wid = tid >> 5;
    const int bin = blockIdx.x;
    const int total = g_cursor[bin];
    const int n = min(total, CAP);
    const bool ovf = total > CAP;

    const uint2* rec = g_records + (size_t)bin * CAP;
    uint2 r[G_PER];
#pragma unroll
    for (int j = 0; j < G_PER; j++) {
        int i = j * G_NT + tid;
        if (i < n) r[j] = __ldcs(rec + i);
    }
    if (tid < NGRP) cnts[tid] = 0;
    for (int i = tid; i < CAPS / 4; i += G_NT) reinterpret_cast<uint4*>(sidx)[i] = make_uint4(0, 0, 0, 0);
    for (int i = tid; i < CAPS / 8; i += G_NT) reinterpret_cast<uint4*>(sc2)[i] = make_uint4(0, 0, 0, 0);
    const unsigned short* fq = reinterpret_cast<const unsigned short*>(p.ang_freq);
    const uint32_t f0 = (uint32_t)fq[0] * 0x10001u, f1 = (uint32_t)fq[1] * 0x10001u, f2 = (uint32_t)fq[2] * 0x10001u;
    __syncthreads();
    if (tid == 0) g_cursor[bin] = 0;
    int rank[G_PER];
#pragma unroll
    for (int j = 0; j < G_PER; j++) {
        int i = j * G_NT + tid;
        if (i < n) rank[j] = atomicAdd(&cnts[r[j].x >> (IDX_BITS + 3)], 1);
    }
    __syncthreads();
    if (wid == 0) {
        static_assert(NGRP == 64, "scan written for 64 groups");
        int c0 = (cnts[2 * lane] + 15) & ~15, c1 = (cnts[2 * lane + 1] + 15) & ~15;
        int s = c0 + c1, inc = s;
#pragma unroll
        for (int o = 1; o < 32; o <<= 1) {
            int t = __shfl_up_sync(0xffffffffu, inc, o);
            if (lane >= o) inc += t;
        }
        gstart[2 * lane] = inc - s;
        gstart[2 * lane + 1] = inc - c1;
        if (lane == 31) gstart[NGRP] = inc;
    }
    __syncthreads();
#pragma unroll
    for (int j = 0; j < G_PER; j++) {
        int i = j * G_NT + tid;
        if (i < n) {
            uint32_t le = r[j].x >> IDX_BITS;
            int pos = gstart[le >> 3] + rank[j];
            sidx[pos] = (r[j].x & IDX_MASK) | (0x1000000u << (le & 7));
            sc2[pos] = (unsigned short)(r[j].y);
        }
    }
    __syncthreads();
    {
        const int nch = gstart[NGRP] >> 2;
        for (int i = tid; i < nch; i += G_NT) {
            uint2 a = reinterpret_cast<const uint2*>(sc2)[i];
            uint4 o;
            o.x = cos_bf16x2(mul_bf16x2(a.x, f0));
            o.y = cos_bf16x2(mul_bf16x2(a.y, f0));
            o.z = cos_bf16x2(mul_bf16x2(a.x, f1));
            o.w = cos_bf16x2(mul_bf16x2(a.y, f1));
            uint2 o2;
            o2.x = cos_bf16x2(mul_bf16x2(a.x, f2));
            o2.y = cos_bf16x2(mul_bf16x2(a.y, f2));
            sc01[i] = o;
            reinterpret_cast<uint2*>(sc2)[i] = o2;
        }
    }
    __syncthreads();

    const int g = lane >> 2, q = lane & 3;
    uint32_t adown[4], aup[4], asbf[NL][2], arb[2];
    {
        const unsigned short* wd = reinterpret_cast<const unsigned short*>(p.w_down);
        const unsigned short* wu = reinterpret_cast<const unsigned short*>(p.w_up);
        const unsigned short* ws = reinterpret_cast<const unsigned short*>(p.w_sbf);
        const unsigned short* wr = reinterpret_cast<const unsigned short*>(p.w_rbf);
        const int cA = 2 * g, cB = 2 * g + 1;
        adown[0] = (uint32_t)wd[(4 * q + 0) * DE + cA] | ((uint32_t)wd[(4 * q + 2) * DE + cA] << 16);
        adown[1] = (uint32_t)wd[(4 * q + 0) * DE + cB] | ((uint32_t)wd[(4 * q + 2) * DE + cB] << 16);
        adown[2] = (uint32_t)wd[(4 * q + 1) * DE + cA] | ((uint32_t)wd[(4 * q + 3) * DE + cA] << 16);
        adown[3] = (uint32_t)wd[(4 * q + 1) * DE + cB] | ((uint32_t)wd[(4 * q + 3) * DE + cB] << 16);
        aup[0] = (uint32_t)wu[(4 * q + 0) * DE + cA] | ((uint32_t)wu[(4 * q + 2) * DE + cA] << 16);
        aup[1] = (uint32_t)wu[(4 * q + 0) * DE + cB] | ((uint32_t)wu[(4 * q + 2) * DE + cB] << 16);
        aup[2] = (uint32_t)wu[(4 * q + 1) * DE + cA] | ((uint32_t)wu[(4 * q + 3) * DE + cA] << 16);
        aup[3] = (uint32_t)wu[(4 * q + 1) * DE + cB] | ((uint32_t)wu[(4 * q + 3) * DE + cB] << 16);
#pragma unroll
        for (int l = 0; l < NL; l++) {
            asbf[l][0] = (uint32_t)ws[((2 * q) * NL + l) * DE + cA] | ((uint32_t)ws[((2 * q + 1) * NL + l) * DE + cA] << 16);
            asbf[l][1] = (uint32_t)ws[((2 * q) * NL + l) * DE + cB] | ((uint32_t)ws[((2 * q + 1) * NL + l) * DE + cB] << 16);
        }
        arb[0] = (uint32_t)wr[(2 * q) * DE + cA] | ((uint32_t)wr[(2 * q + 1) * DE + cA] << 16);
        arb[1] = (uint32_t)wr[(2 * q) * DE + cB] | ((uint32_t)wr[(2 * q + 1) * DE + cB] << 16);
    }
    const float cen0 = ldbf(p.centers + 2 * q), cen1 = ldbf(p.centers + 2 * q + 1);
    const uint32_t* m4 = reinterpret_cast<const uint32_t*>(p.m) + g;
    const int sh = 7 - g;

#pragma unroll 1
    for (int grp = wid; grp < NGRP; grp += G_NT / 32) {
        const int s = gstart[grp], e = gstart[grp + 1];
        const int e0 = bin * NB + grp * 8;
        const int eg = e0 + g;
        const int ea = e0 + 2 * q, eb = ea + 1;
        float dg = (eg < p.E) ? ldbf(p.dist + eg) : 0.f;
        uint32_t ma = (ea < p.E) ? __ldg(m4 + (size_t)ea * 8) : 0u;
        uint32_t mb = (eb < p.E) ? __ldg(m4 + (size_t)eb * 8) : 0u;

        float D[NL][4];
#pragma unroll
        for (int l = 0; l < NL; l++)
#pragma unroll
            for (int c = 0; c < 4; c++) D[l][c] = 0.f;
#pragma unroll 2
        for (int i = s; i < e; i += 16) {
            const int ch = (i >> 2) + q;
            uint4 w = reinterpret_cast<const uint4*>(sidx)[ch];
            uint4 c01 = sc01[ch];
            uint2 c2 = reinterpret_cast<const uint2*>(sc2)[ch];
            uint32_t v0 = __ldg(m4 + (size_t)(w.x & 0xffffffu) * 8);
            uint32_t v1 = __ldg(m4 + (size_t)(w.y & 0xffffffu) * 8);
            uint32_t v2 = __ldg(m4 + (size_t)(w.z & 0xffffffu) * 8);
            uint32_t v3 = __ldg(m4 + (size_t)(w.w & 0xffffffu) * 8);
            uint32_t k01 = prmt(w.x << sh, w.y << sh, 0xFFBB);
            uint32_t k23 = prmt(w.z << sh, w.w << sh, 0xFFBB);
            uint32_t a[4];
            a[0] = prmt(v0, v1, 0x5410);
            a[1] = prmt(v0, v1, 0x7632);
            a[2] = prmt(v2, v3, 0x5410);
            a[3] = prmt(v2, v3, 0x7632);
            mma16816(D[0], a, c01.x & k01, c01.y & k23);
            mma16816(D[1], a, c01.z & k01, c01.w & k23);
            mma16816(D[2], a, c2.x & k01, c2.y & k23);
        }
        const uint32_t brbf = pack_bf16(rbf_val(dg, cen0), rbf_val(dg, cen1));
        float agg[4] = {0.f, 0.f, 0.f, 0.f};
#pragma unroll
        for (int l = 0; l < NL; l++) {
            uint32_t h0 = pack_bf16(D[l][0], D[l][1]);
            uint32_t h1 = pack_bf16(D[l][2], D[l][3]);
            uint32_t l0 = pack_bf16(D[l][0] - bf16lo(h0), D[l][1] - bf16hi(h0));
            uint32_t l1 = pack_bf16(D[l][2] - bf16lo(h1), D[l][3] - bf16hi(h1));
            h0 = movm(h0); h1 = movm(h1); l0 = movm(l0); l1 = movm(l1);
            float S[4] = {0.f, 0.f, 0.f, 0.f};
            float G[4] = {0.f, 0.f, 0.f, 0.f};
            mma16816(S, adown, l0, l1);
            mma16816(S, adown, h0, h1);
            mma1688(G, asbf[l], brbf);
#pragma unroll
            for (int c = 0; c < 4; c++) agg[c] = fmaf(S[c], G[c], agg[c]);
        }
        if (ovf) {
            if (ea < p.E) {
                float2* pa = reinterpret_cast<float2*>(g_ovf + (size_t)ea * DE + 2 * g);
                float2 o = *pa; *pa = make_float2(0.f, 0.f);
                agg[0] += o.x; agg[2] += o.y;
            }
            if (eb < p.E) {
                float2* pb = reinterpret_cast<float2*>(g_ovf + (size_t)eb * DE + 2 * g);
                float2 o = *pb; *pb = make_float2(0.f, 0.f);
                agg[1] += o.x; agg[3] += o.y;
            }
        }
        {
            uint32_t h0 = pack_bf16(agg[0], agg[1]);
            uint32_t h1 = pack_bf16(agg[2], agg[3]);
            uint32_t l0 = pack_bf16(agg[0] - bf16lo(h0), agg[1] - bf16hi(h0));
            uint32_t l1 = pack_bf16(agg[2] - bf16lo(h1), agg[3] - bf16hi(h1));
            h0 = movm(h0); h1 = movm(h1); l0 = movm(l0); l1 = movm(l1);
            float U[4] = {0.f, 0.f, 0.f, 0.f};
            float R[4] = {0.f, 0.f, 0.f, 0.f};
            mma16816(U, aup, l0, l1);
            mma16816(U, aup, h0, h1);
            mma1688(R, arb, brbf);
            uint32_t oa = pack_bf16(bf16lo(ma) + U[0] * R[0], bf16hi(ma) + U[2] * R[2]);
            uint32_t ob = pack_bf16(bf16lo(mb) + U[1] * R[1], bf16hi(mb) + U[3] * R[3]);
            uint32_t* o4 = reinterpret_cast<uint32_t*>(p.out) + g;
            if (ea < p.E) o4[(size_t)ea * 8] = oa;
            if (eb < p.E) o4[(size_t)eb * 8] = ob;
        }
    }
}

}

extern "C" void kernel_launch(void* const* d_in, const int* in_sizes, int n_in,
                              void* d_out, int out_size) {
    Params p;
    p.m = (const __nv_bfloat16*)d_in[0];
    p.idx_in = (const int*)d_in[1];
    p.idx_out = (const int*)d_in[2];
    p.dist = (const __nv_bfloat16*)d_in[3];
    p.angle = (const __nv_bfloat16*)d_in[4];
    p.centers = (const __nv_bfloat16*)d_in[5];
    p.ang_freq = (const __nv_bfloat16*)d_in[6];
    p.w_rbf = (const __nv_bfloat16*)d_in[7];
    p.w_sbf = (const __nv_bfloat16*)d_in[8];
    p.w_down = (const __nv_bfloat16*)d_in[9];
    p.w_up = (const __nv_bfloat16*)d_in[10];
    p.out = (__nv_bfloat16*)d_out;
    p.E = in_sizes[3];
    p.T = in_sizes[1];
    p.nbins = (p.E + NB - 1) / NB;

    const int smem1 = P_TILE * 8 + 2 * BINS_PAD * 4;
    const int smem2 = CAPS * 10;
    static bool init = false;
    if (!init) {
        cudaFuncSetAttribute(k_partition, cudaFuncAttributeMaxDynamicSharedMemorySize, smem1);
        cudaFuncSetAttribute(k_gather, cudaFuncAttributeMaxDynamicSharedMemorySize, smem2);
        init = true;
    }
    int ntiles = (p.T + P_TILE - 1) / P_TILE;
    k_partition<<<ntiles, P_NT, smem1>>>(p);
    k_gather<<<p.nbins, G_NT, smem2>>>(p);
}
```

```cpp
#include <cuda_runtime.h>
#include <cuda_bf16.h>
#include <stdint.h>

namespace {

constexpr int DE = 16;
constexpr int NR = 8;
constexpr int NL = 3;

constexpr int NB_LOG = 9;
constexpr int NB = 1 << NB_LOG;
constexpr int IDX_BITS = 32 - NB_LOG;
constexpr uint32_t IDX_MASK = (1u << IDX_BITS) - 1u;
constexpr int MAX_E = 400000;
constexpr int MAX_BINS = (MAX_E + NB - 1) / NB;
constexpr int BINS_PAD = 1024;
constexpr int CAP = 8960;

constexpr int P_TILE = 8192;
constexpr int P_NT = 1024;
constexpr int P_PER = P_TILE / P_NT;

constexpr int G_NT = 512;
constexpr int G_PER = (CAP + G_NT - 1) / G_NT;
constexpr int NGRP = NB / 8;
constexpr int CAPS = CAP + NGRP * 16;

__device__ uint2 g_records[(size_t)MAX_BINS * CAP];
__device__ int g_cursor[BINS_PAD];
__device__ float g_ovf[(size_t)MAX_BINS * NB * DE];

__device__ __forceinline__ float bf16r(float x) { return __bfloat162float(__float2bfloat16_rn(x)); }
__device__ __forceinline__ float bf16lo(uint32_t v) { return __uint_as_float(v << 16); }
__device__ __forceinline__ float bf16hi(uint32_t v) { return __uint_as_float(v & 0xffff0000u); }
__device__ __forceinline__ float ldbf(const __nv_bfloat16* p) { return __bfloat162float(*p); }

__device__ __forceinline__ uint32_t pack_bf16(float lo, float hi) {
    __nv_bfloat162 v = __floats2bfloat162_rn(lo, hi);
    return *reinterpret_cast<uint32_t*>(&v);
}
__device__ __forceinline__ uint32_t mul_bf16x2(uint32_t a, uint32_t b) {
    __nv_bfloat162 r = __hmul2(*reinterpret_cast<__nv_bfloat162*>(&a), *reinterpret_cast<__nv_bfloat162*>(&b));
    return *reinterpret_cast<uint32_t*>(&r);
}
__device__ __forceinline__ uint32_t sub_bf16x2(uint32_t a, uint32_t b) {
    __nv_bfloat162 r = __hsub2(*reinterpret_cast<__nv_bfloat162*>(&a), *reinterpret_cast<__nv_bfloat162*>(&b));
    return *reinterpret_cast<uint32_t*>(&r);
}
__device__ __forceinline__ uint32_t cos_fast_bf16x2(uint32_t x) {
    return pack_bf16(__cosf(bf16lo(x)), __cosf(bf16hi(x)));
}
__device__ __noinline__ uint32_t cos_slow_bf16x2(uint32_t x) {
    return pack_bf16(cosf(bf16lo(x)), cosf(bf16hi(x)));
}
__device__ __forceinline__ uint32_t rbf_bf16x2(uint32_t dd, uint32_t cc) {
    uint32_t t = sub_bf16x2(dd, cc);
    t = mul_bf16x2(t, t);
    t = mul_bf16x2(t, 0xC120C120u);
    return pack_bf16(__expf(bf16lo(t)), __expf(bf16hi(t)));
}

__device__ __forceinline__ void mma16816(float* d, const uint32_t* a, uint32_t b0, uint32_t b1) {
    asm volatile("mma.sync.aligned.m16n8k16.row.col.f32.bf16.bf16.f32 {%0,%1,%2,%3}, {%4,%5,%6,%7}, {%8,%9}, {%0,%1,%2,%3};"
                 : "+f"(d[0]), "+f"(d[1]), "+f"(d[2]), "+f"(d[3])
                 : "r"(a[0]), "r"(a[1]), "r"(a[2]), "r"(a[3]), "r"(b0), "r"(b1));
}
__device__ __forceinline__ void mma1688(float* d, const uint32_t* a, uint32_t b) {
    asm volatile("mma.sync.aligned.m16n8k8.row.col.f32.bf16.bf16.f32 {%0,%1,%2,%3}, {%4,%5}, {%6}, {%0,%1,%2,%3};"
                 : "+f"(d[0]), "+f"(d[1]), "+f"(d[2]), "+f"(d[3])
                 : "r"(a[0]), "r"(a[1]), "r"(b));
}
__device__ __forceinline__ uint32_t movm(uint32_t a) {
    uint32_t d;
    asm volatile("movmatrix.sync.aligned.m8n8.trans.b16 %0, %1;" : "=r"(d) : "r"(a));
    return d;
}
__device__ __forceinline__ uint32_t prmt(uint32_t a, uint32_t b, uint32_t sel) {
    uint32_t d;
    asm("prmt.b32 %0, %1, %2, %3;" : "=r"(d) : "r"(a), "r"(b), "r"(sel));
    return d;
}

struct Params {
    const __nv_bfloat16* m;
    const int* idx_in;
    const int* idx_out;
    const __nv_bfloat16* dist;
    const __nv_bfloat16* angle;
    const __nv_bfloat16* centers;
    const __nv_bfloat16* ang_freq;
    const __nv_bfloat16* w_rbf;
    const __nv_bfloat16* w_sbf;
    const __nv_bfloat16* w_down;
    const __nv_bfloat16* w_up;
    __nv_bfloat16* out;
    int E, T, nbins, ntiles;
};

__device__ __noinline__ void slow_triplet(const Params* pp, int in, int out, float ang) {
    const Params& p = *pp;
    float mrow[DE], rb[NR], cb[NL];
    for (int k = 0; k < DE; k++) mrow[k] = ldbf(p.m + (size_t)in * DE + k);
    float d = ldbf(p.dist + out);
    for (int r = 0; r < NR; r++) {
        float t = bf16r(d - ldbf(p.centers + r));
        t = bf16r(t * t);
        t = bf16r(-10.0f * t);
        rb[r] = bf16r(__expf(t));
    }
    for (int l = 0; l < NL; l++) cb[l] = bf16r(cosf(bf16r(ldbf(p.ang_freq + l) * ang)));
    for (int c = 0; c < DE; c++) {
        float md = 0.f, s = 0.f;
        for (int k = 0; k < DE; k++) md = fmaf(mrow[k], ldbf(p.w_down + k * DE + c), md);
        for (int r = 0; r < NR; r++)
            for (int l = 0; l < NL; l++) s = fmaf(rb[r] * cb[l], ldbf(p.w_sbf + (r * NL + l) * DE + c), s);
        atomicAdd(&g_ovf[(size_t)out * DE + c], md * s);
    }
}

struct RawTile { int4 a[P_PER / 4]; int4 b[P_PER / 4]; uint2 c[P_PER / 4]; };

__device__ __forceinline__ void load_tile(const Params& p, int tile, int tid, RawTile& t) {
    const int base = tile * P_TILE;
    if (base + P_TILE <= p.T) {
#pragma unroll
        for (int v = 0; v < P_PER / 4; v++) {
            int i = base + (v * P_NT + tid) * 4;
            t.a[v] = __ldcs(reinterpret_cast<const int4*>(p.idx_in + i));
            t.b[v] = __ldcs(reinterpret_cast<const int4*>(p.idx_out + i));
            t.c[v] = __ldcs(reinterpret_cast<const uint2*>(p.angle + i));
        }
    } else {
        const unsigned short* ang = reinterpret_cast<const unsigned short*>(p.angle);
#pragma unroll
        for (int v = 0; v < P_PER / 4; v++) {
            int i = base + (v * P_NT + tid) * 4;
            int a[4], b[4]; uint32_t c[4];
#pragma unroll
            for (int u = 0; u < 4; u++) {
                bool ok = i + u < p.T;
                a[u] = ok ? p.idx_in[i + u] : 0;
                b[u] = ok ? p.idx_out[i + u] : -1;
                c[u] = ok ? (uint32_t)ang[i + u] : 0u;
            }
            t.a[v] = make_int4(a[0], a[1], a[2], a[3]);
            t.b[v] = make_int4(b[0], b[1], b[2], b[3]);
            t.c[v] = make_uint2(c[0] | (c[1] << 16), c[2] | (c[3] << 16));
        }
    }
}

__global__ void __launch_bounds__(P_NT, 1) k_partition(const __grid_constant__ Params p) {
    extern __shared__ __align__(16) unsigned char smem_raw[];
    uint2* stage = reinterpret_cast<uint2*>(smem_raw);
    int* hist = reinterpret_cast<int*>(smem_raw + (size_t)(P_TILE + 8) * 8);
    int* delta = hist + BINS_PAD + 4;
    __shared__ int warp_sums[P_NT / 32];
    static_assert(BINS_PAD == P_NT, "one bin per thread in the scan");

    const int tid = threadIdx.x;
    const int lane = tid & 31, wid = tid >> 5;

    RawTile nxt;
    int tile = blockIdx.x;
    if (tile < p.ntiles) load_tile(p, tile, tid, nxt);
    for (; tile < p.ntiles; tile += gridDim.x) {
        const int n = min(P_TILE, p.T - tile * P_TILE);
        uint32_t rx[P_PER], ry[P_PER];
#pragma unroll
        for (int v = 0; v < P_PER / 4; v++) {
            const int4 a = nxt.a[v], b = nxt.b[v];
            const uint2 c = nxt.c[v];
            rx[v * 4 + 0] = (uint32_t)a.x | ((uint32_t)b.x << IDX_BITS); ry[v * 4 + 0] = (c.x & 0xffffu) | (((uint32_t)b.x >> NB_LOG) << 16);
            rx[v * 4 + 1] = (uint32_t)a.y | ((uint32_t)b.y << IDX_BITS); ry[v * 4 + 1] = (c.x >> 16) | (((uint32_t)b.y >> NB_LOG) << 16);
            rx[v * 4 + 2] = (uint32_t)a.z | ((uint32_t)b.z << IDX_BITS); ry[v * 4 + 2] = (c.y & 0xffffu) | (((uint32_t)b.z >> NB_LOG) << 16);
            rx[v * 4 + 3] = (uint32_t)a.w | ((uint32_t)b.w << IDX_BITS); ry[v * 4 + 3] = (c.y >> 16) | (((uint32_t)b.w >> NB_LOG) << 16);
        }
        if (tile + (int)gridDim.x < p.ntiles) load_tile(p, tile + gridDim.x, tid, nxt);
        hist[tid] = 0;
        if (tid == 0) hist[BINS_PAD] = 0;
        __syncthreads();
        int rank[P_PER];
#pragma unroll
        for (int j = 0; j < P_PER; j++) rank[j] = atomicAdd(&hist[min(ry[j] >> 16, (uint32_t)BINS_PAD)], 1);
        __syncthreads();
        const int c1 = hist[tid];
        int g0 = 0;
        if (c1) g0 = atomicAdd(&g_cursor[tid], c1);
        int inc = c1;
#pragma unroll
        for (int o = 1; o < 32; o <<= 1) {
            int t = __shfl_up_sync(0xffffffffu, inc, o);
            if (lane >= o) inc += t;
        }
        if (lane == 31) warp_sums[wid] = inc;
        __syncthreads();
        int woff;
        {
            int ws = warp_sums[lane];
            int winc = ws;
#pragma unroll
            for (int o = 1; o < 32; o <<= 1) {
                int t = __shfl_up_sync(0xffffffffu, winc, o);
                if (lane >= o) winc += t;
            }
            woff = __shfl_sync(0xffffffffu, winc - ws, wid);
        }
        const int e0 = woff + inc - c1;
        hist[tid] = e0;
        if (tid == 0) hist[BINS_PAD] = P_TILE;
        __syncthreads();
#pragma unroll
        for (int j = 0; j < P_PER; j++) {
            int pos = min(hist[min(ry[j] >> 16, (uint32_t)BINS_PAD)] + rank[j], P_TILE);
            stage[pos] = make_uint2(rx[j], ry[j]);
        }
        delta[tid] = g0 - e0;
        __syncthreads();
#pragma unroll
        for (int j = 0; j < P_PER; j++) {
            const int i = j * P_NT + tid;
            if (i < n) {
                uint2 r = stage[i];
                int bin = r.y >> 16;
                int d = i + delta[bin];
                if (d < CAP) {
                    g_records[(size_t)bin * CAP + d] = r;
                } else {
                    slow_triplet(&p, (int)(r.x & IDX_MASK), (bin << NB_LOG) | (int)(r.x >> IDX_BITS), bf16lo(r.y & 0xffffu));
                }
            }
        }
    }
}

__global__ void __launch_bounds__(G_NT, 2) k_gather(const __grid_constant__ Params p) {
    extern __shared__ __align__(16) unsigned char smem_raw[];
    uint32_t* sidx = reinterpret_cast<uint32_t*>(smem_raw);
    uint4* sc01 = reinterpret_cast<uint4*>(smem_raw + (size_t)(CAPS + 8) * 4);
    unsigned short* sc2 = reinterpret_cast<unsigned short*>(smem_raw + (size_t)(CAPS + 8) * 4 + (size_t)CAPS * 4);
    __shared__ int cnts[NGRP + 1];
    __shared__ int gstart[NGRP + 2];

    const int tid = threadIdx.x;
    const int lane = tid & 31, wid = tid >> 5;
    const int bin = blockIdx.x;
    const int total = g_cursor[bin];
    const int n = min(total, CAP);
    const bool ovf = total > CAP;

    const uint2* rec = g_records + (size_t)bin * CAP + tid;
    uint2 r[G_PER];
#pragma unroll
    for (int j = 0; j < G_PER; j++) {
        r[j] = make_uint2(0u, 0xffffffffu);
        if (j * G_NT + tid < n) r[j] = __ldcs(rec + j * G_NT);
    }
    if (tid <= NGRP) cnts[tid] = 0;
    for (int i = tid; i < CAPS / 4; i += G_NT) reinterpret_cast<uint4*>(sidx)[i] = make_uint4(0, 0, 0, 0);
    for (int i = tid; i < CAPS / 8; i += G_NT) reinterpret_cast<uint4*>(sc2)[i] = make_uint4(0, 0, 0, 0);
    const unsigned short* fq = reinterpret_cast<const unsigned short*>(p.ang_freq);
    const uint32_t f0 = (uint32_t)fq[0] * 0x10001u, f1 = (uint32_t)fq[1] * 0x10001u, f2 = (uint32_t)fq[2] * 0x10001u;
    __syncthreads();
    if (tid == 0) g_cursor[bin] = 0;
#pragma unroll
    for (int j = 0; j < G_PER; j++) {
        uint32_t grp = (r[j].y == 0xffffffffu) ? (uint32_t)NGRP : (r[j].x >> (IDX_BITS + 3));
        uint32_t rk = (uint32_t)atomicAdd(&cnts[grp], 1);
        r[j].y = (r[j].y & 0xffffu) | (rk << 16) | ((grp == NGRP) ? 0x80000000u : 0u);
    }
    __syncthreads();
    if (wid == 0) {
        static_assert(NGRP == 64, "scan written for 64 groups");
        int c0 = (cnts[2 * lane] + 15) & ~15, c1 = (cnts[2 * lane + 1] + 15) & ~15;
        int s = c0 + c1, inc = s;
#pragma unroll
        for (int o = 1; o < 32; o <<= 1) {
            int t = __shfl_up_sync(0xffffffffu, inc, o);
            if (lane >= o) inc += t;
        }
        gstart[2 * lane] = inc - s;
        gstart[2 * lane + 1] = inc - c1;
        if (lane == 31) gstart[NGRP] = inc;
    }
    __syncthreads();
#pragma unroll
    for (int j = 0; j < G_PER; j++) {
        uint32_t le = r[j].x >> IDX_BITS;
        uint32_t pos = min((uint32_t)gstart[le >> 3] + (r[j].y >> 16), (uint32_t)CAPS);
        sidx[pos] = ((r[j].x & IDX_MASK) << 5) | (0x1000000u << (le & 7));
        sc2[pos] = (unsigned short)(r[j].y);
    }
    __syncthreads();
    {
        const int nch = gstart[NGRP] >> 2;
        for (int i = tid; i < nch; i += G_NT) {
            uint2 a = reinterpret_cast<const uint2*>(sc2)[i];
            uint32_t x0 = mul_bf16x2(a.x, f0), x1 = mul_bf16x2(a.y, f0);
            uint32_t x2 = mul_bf16x2(a.x, f1), x3 = mul_bf16x2(a.y, f1);
            uint32_t x4 = mul_bf16x2(a.x, f2), x5 = mul_bf16x2(a.y, f2);
            uint32_t t = (x0 | x1 | x2 | x3 | x4 | x5) & 0x7fff7fffu;
            uint4 o; uint2 o2;
            if ((t >> 16) < 0x4380u && (t & 0xffffu) < 0x4380u) {
                o.x = cos_fast_bf16x2(x0); o.y = cos_fast_bf16x2(x1);
                o.z = cos_fast_bf16x2(x2); o.w = cos_fast_bf16x2(x3);
                o2.x = cos_fast_bf16x2(x4); o2.y = cos_fast_bf16x2(x5);
            } else {
                o.x = cos_slow_bf16x2(x0); o.y = cos_slow_bf16x2(x1);
                o.z = cos_slow_bf16x2(x2); o.w = cos_slow_bf16x2(x3);
                o2.x = cos_slow_bf16x2(x4); o2.y = cos_slow_bf16x2(x5);
            }
            sc01[i] = o;
            reinterpret_cast<uint2*>(sc2)[i] = o2;
        }
    }
    __syncthreads();

    const int g = lane >> 2, q = lane & 3;
    uint32_t adown[4], aup[4], asbf[NL][2], arb[2];
    {
        const unsigned short* wd = reinterpret_cast<const unsigned short*>(p.w_down);
        const unsigned short* wu = reinterpret_cast<const unsigned short*>(p.w_up);
        const unsigned short* ws = reinterpret_cast<const unsigned short*>(p.w_sbf);
        const unsigned short* wr = reinterpret_cast<const unsigned short*>(p.w_rbf);
        const int cA = 2 * g, cB = 2 * g + 1;
        adown[0] = (uint32_t)wd[(4 * q + 0) * DE + cA] | ((uint32_t)wd[(4 * q + 2) * DE + cA] << 16);
        adown[1] = (uint32_t)wd[(4 * q + 0) * DE + cB] | ((uint32_t)wd[(4 * q + 2) * DE + cB] << 16);
        adown[2] = (uint32_t)wd[(4 * q + 1) * DE + cA] | ((uint32_t)wd[(4 * q + 3) * DE + cA] << 16);
        adown[3] = (uint32_t)wd[(4 * q + 1) * DE + cB] | ((uint32_t)wd[(4 * q + 3) * DE + cB] << 16);
        aup[0] = (uint32_t)wu[(4 * q + 0) * DE + cA] | ((uint32_t)wu[(4 * q + 2) * DE + cA] << 16);
        aup[1] = (uint32_t)wu[(4 * q + 0) * DE + cB] | ((uint32_t)wu[(4 * q + 2) * DE + cB] << 16);
        aup[2] = (uint32_t)wu[(4 * q + 1) * DE + cA] | ((uint32_t)wu[(4 * q + 3) * DE + cA] << 16);
        aup[3] = (uint32_t)wu[(4 * q + 1) * DE + cB] | ((uint32_t)wu[(4 * q + 3) * DE + cB] << 16);
#pragma unroll
        for (int l = 0; l < NL; l++) {
            asbf[l][0] = (uint32_t)ws[((2 * q) * NL + l) * DE + cA] | ((uint32_t)ws[((2 * q + 1) * NL + l) * DE + cA] << 16);
            asbf[l][1] = (uint32_t)ws[((2 * q) * NL + l) * DE + cB] | ((uint32_t)ws[((2 * q + 1) * NL + l) * DE + cB] << 16);
        }
        arb[0] = (uint32_t)wr[(2 * q) * DE + cA] | ((uint32_t)wr[(2 * q + 1) * DE + cA] << 16);
        arb[1] = (uint32_t)wr[(2 * q) * DE + cB] | ((uint32_t)wr[(2 * q + 1) * DE + cB] << 16);
    }
    const uint32_t cen = reinterpret_cast<const uint32_t*>(p.centers)[q];
    const unsigned char* mb = reinterpret_cast<const unsigned char*>(p.m);
    const unsigned short* dist16 = reinterpret_cast<const unsigned short*>(p.dist);
    const uint32_t g4 = 4u * g;
    const int sh = 7 - g;

#pragma unroll 1
    for (int grp = wid; grp < NGRP; grp += G_NT / 32) {
        const int s = gstart[grp], e = gstart[grp + 1];
        const int e0 = bin * NB + grp * 8;
        const int eg = e0 + g;
        const int ea = e0 + 2 * q;
        uint32_t dg = (eg < p.E) ? (uint32_t)dist16[eg] : 0u;
        const uint32_t moff = (uint32_t)ea * 32u + g4;
        uint32_t ma = (ea < p.E) ? __ldg(reinterpret_cast<const uint32_t*>(mb + moff)) : 0u;
        uint32_t mbv = (ea + 1 < p.E) ? __ldg(reinterpret_cast<const uint32_t*>(mb + moff + 32)) : 0u;

        float D[NL][4];
#pragma unroll
        for (int l = 0; l < NL; l++)
#pragma unroll
            for (int c = 0; c < 4; c++) D[l][c] = 0.f;
#pragma unroll 2
        for (int ch = (s >> 2) + q; ch < (e >> 2); ch += 4) {
            uint4 w = reinterpret_cast<const uint4*>(sidx)[ch];
            uint4 c01 = sc01[ch];
            uint2 c2 = reinterpret_cast<const uint2*>(sc2)[ch];
            uint32_t v0 = __ldg(reinterpret_cast<const uint32_t*>(mb + ((w.x & 0xffffffu) | g4)));
            uint32_t v1 = __ldg(reinterpret_cast<const uint32_t*>(mb + ((w.y & 0xffffffu) | g4)));
            uint32_t v2 = __ldg(reinterpret_cast<const uint32_t*>(mb + ((w.z & 0xffffffu) | g4)));
            uint32_t v3 = __ldg(reinterpret_cast<const uint32_t*>(mb + ((w.w & 0xffffffu) | g4)));
            uint32_t k01 = prmt(w.x << sh, w.y << sh, 0xFFBB);
            uint32_t k23 = prmt(w.z << sh, w.w << sh, 0xFFBB);
            uint32_t a[4];
            a[0] = prmt(v0, v1, 0x5410);
            a[1] = prmt(v0, v1, 0x7632);
            a[2] = prmt(v2, v3, 0x5410);
            a[3] = prmt(v2, v3, 0x7632);
            mma16816(D[0], a, c01.x & k01, c01.y & k23);
            mma16816(D[1], a, c01.z & k01, c01.w & k23);
            mma16816(D[2], a, c2.x & k01, c2.y & k23);
        }
        const uint32_t brbf = rbf_bf16x2(dg * 0x10001u, cen);
        float agg[4] = {0.f, 0.f, 0.f, 0.f};
#pragma unroll
        for (int l = 0; l < NL; l++) {
            uint32_t h0 = pack_bf16(D[l][0], D[l][1]);
            uint32_t h1 = pack_bf16(D[l][2], D[l][3]);
            uint32_t l0 = pack_bf16(D[l][0] - bf16lo(h0), D[l][1] - bf16hi(h0));
            uint32_t l1 = pack_bf16(D[l][2] - bf16lo(h1), D[l][3] - bf16hi(h1));
            h0 = movm(h0); h1 = movm(h1); l0 = movm(l0); l1 = movm(l1);
            float S[4] = {0.f, 0.f, 0.f, 0.f};
            float G[4] = {0.f, 0.f, 0.f, 0.f};
            mma16816(S, adown, l0, l1);
            mma16816(S, adown, h0, h1);
            mma1688(G, asbf[l], brbf);
#pragma unroll
            for (int c = 0; c < 4; c++) agg[c] = fmaf(S[c], G[c], agg[c]);
        }
        if (ovf) {
            if (ea < p.E) {
                float2* pa = reinterpret_cast<float2*>(g_ovf + (size_t)ea * DE + 2 * g);
                float2 o = *pa; *pa = make_float2(0.f, 0.f);
                agg[0] += o.x; agg[2] += o.y;
            }
            if (ea + 1 < p.E) {
                float2* pb = reinterpret_cast<float2*>(g_ovf + (size_t)(ea + 1) * DE + 2 * g);
                float2 o = *pb; *pb = make_float2(0.f, 0.f);
                agg[1] += o.x; agg[3] += o.y;
            }
        }
        {
            uint32_t h0 = pack_bf16(agg[0], agg[1]);
            uint32_t h1 = pack_bf16(agg[2], agg[3]);
            uint32_t l0 = pack_bf16(agg[0] - bf16lo(h0), agg[1] - bf16hi(h0));
            uint32_t l1 = pack_bf16(agg[2] - bf16lo(h1), agg[3] - bf16hi(h1));
            h0 = movm(h0); h1 = movm(h1); l0 = movm(l0); l1 = movm(l1);
            float U[4] = {0.f, 0.f, 0.f, 0.f};
            float R[4] = {0.f, 0.f, 0.f, 0.f};
            mma16816(U, aup, l0, l1);
            mma16816(U, aup, h0, h1);
            mma1688(R, arb, brbf);
            uint32_t oa = pack_bf16(fmaf(U[0], R[0], bf16lo(ma)), fmaf(U[2], R[2], bf16hi(ma)));
            uint32_t ob = pack_bf16(fmaf(U[1], R[1], bf16lo(mbv)), fmaf(U[3], R[3], bf16hi(mbv)));
            unsigned char* ob8 = reinterpret_cast<unsigned char*>(p.out);
            if (ea < p.E) *reinterpret_cast<uint32_t*>(ob8 + moff) = oa;
            if (ea + 1 < p.E) *reinterpret_cast<uint32_t*>(ob8 + moff + 32) = ob;
        }
    }
}

}

extern "C" void kernel_launch(void* const* d_in, const int* in_sizes, int n_in,
                              void* d_out, int out_size) {
    Params p;
    p.m = (const __nv_bfloat16*)d_in[0];
    p.idx_in = (const int*)d_in[1];
    p.idx_out = (const int*)d_in[2];
    p.dist = (const __nv_bfloat16*)d_in[3];
    p.angle = (const __nv_bfloat16*)d_in[4];
    p.centers = (const __nv_bfloat16*)d_in[5];
    p.ang_freq = (const __nv_bfloat16*)d_in[6];
    p.w_rbf = (const __nv_bfloat16*)d_in[7];
    p.w_sbf = (const __nv_bfloat16*)d_in[8];
    p.w_down = (const __nv_bfloat16*)d_in[9];
    p.w_up = (const __nv_bfloat16*)d_in[10];
    p.out = (__nv_bfloat16*)d_out;
    p.E = in_sizes[3];
    p.T = in_sizes[1];
    p.nbins = (p.E + NB - 1) / NB;
    p.ntiles = (p.T + P_TILE - 1) / P_TILE;

    const int smem1 = (P_TILE + 8) * 8 + (2 * BINS_PAD + 4) * 4;
    const int smem2 = (CAPS + 8) * 4 + CAPS * 4 + (CAPS + 8) * 2;
    static int nsm = 0;
    if (!nsm) {
        cudaFuncSetAttribute(k_partition, cudaFuncAttributeMaxDynamicSharedMemorySize, smem1);
        cudaFuncSetAttribute(k_gather, cudaFuncAttributeMaxDynamicSharedMemorySize, smem2);
        int dev = 0;
        cudaGetDevice(&dev);
        cudaDeviceGetAttribute(&nsm, cudaDevAttrMultiProcessorCount, dev);
    }
    int g1 = p.ntiles < nsm ? p.ntiles : nsm;
    k_partition<<<g1, P_NT, smem1>>>(p);
    k_gather<<<p.nbins, G_NT, smem2>>>(p);
}
```

```cpp
#include <cuda_runtime.h>
#include <cuda_bf16.h>
#include <stdint.h>

namespace {

constexpr int DE = 16;
constexpr int NR = 8;
constexpr int NL = 3;

constexpr int NB_LOG = 9;
constexpr int NB = 1 << NB_LOG;
constexpr int IDX_BITS = 32 - NB_LOG;
constexpr uint32_t IDX_MASK = (1u << IDX_BITS) - 1u;
constexpr int MAX_E = 400000;
constexpr int MAX_BINS = (MAX_E + NB - 1) / NB;
constexpr int BINS_PAD = 1024;
constexpr int CAP = 8960;

constexpr int P_TILE = 8192;
constexpr int P_NT = 1024;
constexpr int P_PER = P_TILE / P_NT;

constexpr int G_NT = 512;
constexpr int G_PER = (CAP + G_NT - 1) / G_NT;
constexpr int NGRP = NB / 8;
constexpr int CAPS = CAP + NGRP * 16;

__device__ uint2 g_records[(size_t)MAX_BINS * CAP];
__device__ int g_cursor[BINS_PAD];
__device__ float g_ovf[(size_t)MAX_BINS * NB * DE];

__device__ __forceinline__ float bf16r(float x) { return __bfloat162float(__float2bfloat16_rn(x)); }
__device__ __forceinline__ float bf16lo(uint32_t v) { return __uint_as_float(v << 16); }
__device__ __forceinline__ float bf16hi(uint32_t v) { return __uint_as_float(v & 0xffff0000u); }
__device__ __forceinline__ float ldbf(const __nv_bfloat16* p) { return __bfloat162float(*p); }

__device__ __forceinline__ uint32_t pack_bf16(float lo, float hi) {
    __nv_bfloat162 v = __floats2bfloat162_rn(lo, hi);
    return *reinterpret_cast<uint32_t*>(&v);
}
__device__ __forceinline__ uint32_t mul_bf16x2(uint32_t a, uint32_t b) {
    __nv_bfloat162 r = __hmul2(*reinterpret_cast<__nv_bfloat162*>(&a), *reinterpret_cast<__nv_bfloat162*>(&b));
    return *reinterpret_cast<uint32_t*>(&r);
}
__device__ __forceinline__ uint32_t sub_bf16x2(uint32_t a, uint32_t b) {
    __nv_bfloat162 r = __hsub2(*reinterpret_cast<__nv_bfloat162*>(&a), *reinterpret_cast<__nv_bfloat162*>(&b));
    return *reinterpret_cast<uint32_t*>(&r);
}
__device__ __forceinline__ uint32_t max_bf16x2(uint32_t a, uint32_t b) {
    return __vmaxu2(a, b);
}
__device__ __forceinline__ uint32_t cos_fast_bf16x2(uint32_t x) {
    return pack_bf16(__cosf(bf16lo(x)), __cosf(bf16hi(x)));
}
__device__ __noinline__ uint32_t cos_slow_bf16x2(uint32_t x) {
    return pack_bf16(cosf(bf16lo(x)), cosf(bf16hi(x)));
}
__device__ __forceinline__ uint32_t rbf_bf16x2(uint32_t dd, uint32_t cc) {
    uint32_t t = sub_bf16x2(dd, cc);
    t = mul_bf16x2(t, t);
    t = mul_bf16x2(t, 0xC120C120u);
    return pack_bf16(__expf(bf16lo(t)), __expf(bf16hi(t)));
}

__device__ __forceinline__ void mma16816(float* d, const uint32_t* a, uint32_t b0, uint32_t b1) {
    asm volatile("mma.sync.aligned.m16n8k16.row.col.f32.bf16.bf16.f32 {%0,%1,%2,%3}, {%4,%5,%6,%7}, {%8,%9}, {%0,%1,%2,%3};"
                 : "+f"(d[0]), "+f"(d[1]), "+f"(d[2]), "+f"(d[3])
                 : "r"(a[0]), "r"(a[1]), "r"(a[2]), "r"(a[3]), "r"(b0), "r"(b1));
}
__device__ __forceinline__ void mma1688(float* d, const uint32_t* a, uint32_t b) {
    asm volatile("mma.sync.aligned.m16n8k8.row.col.f32.bf16.bf16.f32 {%0,%1,%2,%3}, {%4,%5}, {%6}, {%0,%1,%2,%3};"
                 : "+f"(d[0]), "+f"(d[1]), "+f"(d[2]), "+f"(d[3])
                 : "r"(a[0]), "r"(a[1]), "r"(b));
}
__device__ __forceinline__ uint32_t movm(uint32_t a) {
    uint32_t d;
    asm volatile("movmatrix.sync.aligned.m8n8.trans.b16 %0, %1;" : "=r"(d) : "r"(a));
    return d;
}
__device__ __forceinline__ uint32_t prmt(uint32_t a, uint32_t b, uint32_t sel) {
    uint32_t d;
    asm("prmt.b32 %0, %1, %2, %3;" : "=r"(d) : "r"(a), "r"(b), "r"(sel));
    return d;
}

struct Params {
    const __nv_bfloat16* m;
    const int* idx_in;
    const int* idx_out;
    const __nv_bfloat16* dist;
    const __nv_bfloat16* angle;
    const __nv_bfloat16* centers;
    const __nv_bfloat16* ang_freq;
    const __nv_bfloat16* w_rbf;
    const __nv_bfloat16* w_sbf;
    const __nv_bfloat16* w_down;
    const __nv_bfloat16* w_up;
    __nv_bfloat16* out;
    int E, T, nbins, ntiles;
};

__device__ __noinline__ void slow_bin(const Params* pp, int bin) {
    const Params& p = *pp;
    for (int t = threadIdx.x; t < p.T; t += blockDim.x) {
        const int out = p.idx_out[t];
        if ((out >> NB_LOG) != bin) continue;
        const int in = p.idx_in[t];
        const float ang = ldbf(p.angle + t);
        float mrow[DE], rb[NR], cb[NL];
        for (int k = 0; k < DE; k++) mrow[k] = ldbf(p.m + (size_t)in * DE + k);
        float d = ldbf(p.dist + out);
        for (int r = 0; r < NR; r++) {
            float u = bf16r(d - ldbf(p.centers + r));
            u = bf16r(u * u);
            u = bf16r(-10.0f * u);
            rb[r] = bf16r(__expf(u));
        }
        for (int l = 0; l < NL; l++) cb[l] = bf16r(cosf(bf16r(ldbf(p.ang_freq + l) * ang)));
        for (int c = 0; c < DE; c++) {
            float md = 0.f, s = 0.f;
            for (int k = 0; k < DE; k++) md = fmaf(mrow[k], ldbf(p.w_down + k * DE + c), md);
            for (int r = 0; r < NR; r++)
                for (int l = 0; l < NL; l++) s = fmaf(rb[r] * cb[l], ldbf(p.w_sbf + (r * NL + l) * DE + c), s);
            atomicAdd(&g_ovf[(size_t)out * DE + c], md * s);
        }
    }
    __threadfence();
}

struct RawTile { int4 a[P_PER / 4]; int4 b[P_PER / 4]; uint2 c[P_PER / 4]; };

__device__ __forceinline__ void load_tile(const Params& p, int tile, int tid, RawTile& t) {
    const int base = tile * P_TILE;
    if (base + P_TILE <= p.T) {
#pragma unroll
        for (int v = 0; v < P_PER / 4; v++) {
            int i = base + (v * P_NT + tid) * 4;
            t.a[v] = __ldcs(reinterpret_cast<const int4*>(p.idx_in + i));
            t.b[v] = __ldcs(reinterpret_cast<const int4*>(p.idx_out + i));
            t.c[v] = __ldcs(reinterpret_cast<const uint2*>(p.angle + i));
        }
    } else {
        const unsigned short* ang = reinterpret_cast<const unsigned short*>(p.angle);
#pragma unroll
        for (int v = 0; v < P_PER / 4; v++) {
            int i = base + (v * P_NT + tid) * 4;
            int a[4], b[4]; uint32_t c[4];
#pragma unroll
            for (int u = 0; u < 4; u++) {
                bool ok = i + u < p.T;
                a[u] = ok ? p.idx_in[i + u] : 0;
                b[u] = ok ? p.idx_out[i + u] : -1;
                c[u] = ok ? (uint32_t)ang[i + u] : 0u;
            }
            t.a[v] = make_int4(a[0], a[1], a[2], a[3]);
            t.b[v] = make_int4(b[0], b[1], b[2], b[3]);
            t.c[v] = make_uint2(c[0] | (c[1] << 16), c[2] | (c[3] << 16));
        }
    }
}

__global__ void __launch_bounds__(P_NT, 1) k_partition(const __grid_constant__ Params p) {
    extern __shared__ __align__(16) unsigned char smem_raw[];
    uint2* stage = reinterpret_cast<uint2*>(smem_raw);
    int* hist = reinterpret_cast<int*>(smem_raw + (size_t)(P_TILE + 8) * 8);
    int* delta = hist + BINS_PAD + 4;
    __shared__ int warp_sums[P_NT / 32];
    static_assert(BINS_PAD == P_NT, "one bin per thread in the scan");

    const int tid = threadIdx.x;
    const int lane = tid & 31, wid = tid >> 5;

    RawTile nxt;
    int tile = blockIdx.x;
    if (tile < p.ntiles) load_tile(p, tile, tid, nxt);
    for (; tile < p.ntiles; tile += gridDim.x) {
        const int n = min(P_TILE, p.T - tile * P_TILE);
        uint32_t rx[P_PER], ry[P_PER];
#pragma unroll
        for (int v = 0; v < P_PER / 4; v++) {
            const int4 a = nxt.a[v], b = nxt.b[v];
            const uint2 c = nxt.c[v];
            rx[v * 4 + 0] = (uint32_t)a.x | ((uint32_t)b.x << IDX_BITS); ry[v * 4 + 0] = (c.x & 0xffffu) | (((uint32_t)b.x >> NB_LOG) << 16);
            rx[v * 4 + 1] = (uint32_t)a.y | ((uint32_t)b.y << IDX_BITS); ry[v * 4 + 1] = (c.x >> 16) | (((uint32_t)b.y >> NB_LOG) << 16);
            rx[v * 4 + 2] = (uint32_t)a.z | ((uint32_t)b.z << IDX_BITS); ry[v * 4 + 2] = (c.y & 0xffffu) | (((uint32_t)b.z >> NB_LOG) << 16);
            rx[v * 4 + 3] = (uint32_t)a.w | ((uint32_t)b.w << IDX_BITS); ry[v * 4 + 3] = (c.y >> 16) | (((uint32_t)b.w >> NB_LOG) << 16);
        }
        if (tile + (int)gridDim.x < p.ntiles) load_tile(p, tile + gridDim.x, tid, nxt);
        hist[tid] = 0;
        if (tid == 0) hist[BINS_PAD] = 0;
        __syncthreads();
        int rank[P_PER];
#pragma unroll
        for (int j = 0; j < P_PER; j++) rank[j] = atomicAdd(&hist[min(ry[j] >> 16, (uint32_t)BINS_PAD)], 1);
        __syncthreads();
        const int c1 = hist[tid];
        int g0 = 0;
        if (c1) g0 = atomicAdd(&g_cursor[tid], c1);
        int inc = c1;
#pragma unroll
        for (int o = 1; o < 32; o <<= 1) {
            int t = __shfl_up_sync(0xffffffffu, inc, o);
            if (lane >= o) inc += t;
        }
        if (lane == 31) warp_sums[wid] = inc;
        __syncthreads();
        int woff;
        {
            int ws = warp_sums[lane];
            int winc = ws;
#pragma unroll
            for (int o = 1; o < 32; o <<= 1) {
                int t = __shfl_up_sync(0xffffffffu, winc, o);
                if (lane >= o) winc += t;
            }
            woff = __shfl_sync(0xffffffffu, winc - ws, wid);
        }
        const int e0 = woff + inc - c1;
        hist[tid] = e0;
        if (tid == 0) hist[BINS_PAD] = P_TILE;
        __syncthreads();
#pragma unroll
        for (int j = 0; j < P_PER; j++) {
            int pos = min(hist[min(ry[j] >> 16, (uint32_t)BINS_PAD)] + rank[j], P_TILE);
            stage[pos] = make_uint2(rx[j], ry[j]);
        }
        delta[tid] = g0 - e0;
        __syncthreads();
#pragma unroll
        for (int j = 0; j < P_PER; j++) {
            const int i = j * P_NT + tid;
            if (i < n) {
                uint2 r = stage[i];
                int bin = r.y >> 16;
                int d = i + delta[bin];
                if (d < CAP) g_records[(size_t)bin * CAP + d] = r;
            }
        }
    }
}

__global__ void __launch_bounds__(G_NT, 2) k_gather(const __grid_constant__ Params p) {
    extern __shared__ __align__(16) unsigned char smem_raw[];
    uint32_t* sidx = reinterpret_cast<uint32_t*>(smem_raw);
    uint4* sc01 = reinterpret_cast<uint4*>(smem_raw + (size_t)(CAPS + 8) * 4);
    unsigned short* sc2 = reinterpret_cast<unsigned short*>(smem_raw + (size_t)(CAPS + 8) * 4 + (size_t)CAPS * 4);
    __shared__ int cnts[NGRP + 1];
    __shared__ int gstart[NGRP + 2];

    const int tid = threadIdx.x;
    const int lane = tid & 31, wid = tid >> 5;
    const int bin = blockIdx.x;
    const int total = g_cursor[bin];
    const bool ovf = total > CAP;
    const int n = ovf ? 0 : total;
    if (ovf) slow_bin(&p, bin);

    const uint2* rec = g_records + (size_t)bin * CAP + tid;
    uint2 r[G_PER];
#pragma unroll
    for (int j = 0; j < G_PER; j++) {
        r[j] = make_uint2(0u, 0xffffffffu);
        if (j * G_NT + tid < n) r[j] = __ldcs(rec + j * G_NT);
    }
    if (tid <= NGRP) cnts[tid] = 0;
    for (int i = tid; i < CAPS / 4; i += G_NT) reinterpret_cast<uint4*>(sidx)[i] = make_uint4(0, 0, 0, 0);
    for (int i = tid; i < CAPS / 8; i += G_NT) reinterpret_cast<uint4*>(sc2)[i] = make_uint4(0, 0, 0, 0);
    const unsigned short* fq = reinterpret_cast<const unsigned short*>(p.ang_freq);
    const uint32_t f0 = (uint32_t)fq[0] * 0x10001u, f1 = (uint32_t)fq[1] * 0x10001u, f2 = (uint32_t)fq[2] * 0x10001u;
    const uint32_t fmaxp = max(max(f0 & 0x7fff7fffu, f1 & 0x7fff7fffu), f2 & 0x7fff7fffu);
    __syncthreads();
    if (tid == 0) g_cursor[bin] = 0;
#pragma unroll
    for (int j = 0; j < G_PER; j++) {
        uint32_t grp = (r[j].y == 0xffffffffu) ? (uint32_t)NGRP : (r[j].x >> (IDX_BITS + 3));
        uint32_t rk = (uint32_t)atomicAdd(&cnts[grp], 1);
        r[j].y = (r[j].y & 0xffffu) | (rk << 16) | ((grp == NGRP) ? 0x80000000u : 0u);
    }
    __syncthreads();
    if (wid == 0) {
        static_assert(NGRP == 64, "scan written for 64 groups");
        int c0 = (cnts[2 * lane] + 15) & ~15, c1 = (cnts[2 * lane + 1] + 15) & ~15;
        int s = c0 + c1, inc = s;
#pragma unroll
        for (int o = 1; o < 32; o <<= 1) {
            int t = __shfl_up_sync(0xffffffffu, inc, o);
            if (lane >= o) inc += t;
        }
        gstart[2 * lane] = inc - s;
        gstart[2 * lane + 1] = inc - c1;
        if (lane == 31) gstart[NGRP] = inc;
    }
    __syncthreads();
#pragma unroll
    for (int j = 0; j < G_PER; j++) {
        uint32_t le = r[j].x >> IDX_BITS;
        uint32_t pos = min((uint32_t)gstart[le >> 3] + (r[j].y >> 16), (uint32_t)CAPS);
        sidx[pos] = ((r[j].x & IDX_MASK) << 5) | (0x1000000u << (le & 7));
        sc2[pos] = (unsigned short)(r[j].y);
    }
    __syncthreads();
    {
        const int nch = gstart[NGRP] >> 2;
        for (int i = tid; i < nch; i += G_NT) {
            uint2 a = reinterpret_cast<const uint2*>(sc2)[i];
            uint32_t x0 = mul_bf16x2(a.x, f0), x1 = mul_bf16x2(a.y, f0);
            uint32_t x2 = mul_bf16x2(a.x, f1), x3 = mul_bf16x2(a.y, f1);
            uint32_t x4 = mul_bf16x2(a.x, f2), x5 = mul_bf16x2(a.y, f2);
            uint32_t t = mul_bf16x2(max_bf16x2(a.x & 0x7fff7fffu, a.y & 0x7fff7fffu), fmaxp);
            uint4 o; uint2 o2;
            if ((t >> 16) < 0x4300u && (t & 0xffffu) < 0x4300u) {
                o.x = cos_fast_bf16x2(x0); o.y = cos_fast_bf16x2(x1);
                o.z = cos_fast_bf16x2(x2); o.w = cos_fast_bf16x2(x3);
                o2.x = cos_fast_bf16x2(x4); o2.y = cos_fast_bf16x2(x5);
            } else {
                o.x = cos_slow_bf16x2(x0); o.y = cos_slow_bf16x2(x1);
                o.z = cos_slow_bf16x2(x2); o.w = cos_slow_bf16x2(x3);
                o2.x = cos_slow_bf16x2(x4); o2.y = cos_slow_bf16x2(x5);
            }
            sc01[i] = o;
            reinterpret_cast<uint2*>(sc2)[i] = o2;
        }
    }
    __syncthreads();

    const int g = lane >> 2, q = lane & 3;
    uint32_t adown[4], aup[4], asbf[NL][2], arb[2];
    {
        const unsigned short* wd = reinterpret_cast<const unsigned short*>(p.w_down);
        const unsigned short* wu = reinterpret_cast<const unsigned short*>(p.w_up);
        const unsigned short* ws = reinterpret_cast<const unsigned short*>(p.w_sbf);
        const unsigned short* wr = reinterpret_cast<const unsigned short*>(p.w_rbf);
        const int cA = 2 * g, cB = 2 * g + 1;
        adown[0] = (uint32_t)wd[(4 * q + 0) * DE + cA] | ((uint32_t)wd[(4 * q + 2) * DE + cA] << 16);
        adown[1] = (uint32_t)wd[(4 * q + 0) * DE + cB] | ((uint32_t)wd[(4 * q + 2) * DE + cB] << 16);
        adown[2] = (uint32_t)wd[(4 * q + 1) * DE + cA] | ((uint32_t)wd[(4 * q + 3) * DE + cA] << 16);
        adown[3] = (uint32_t)wd[(4 * q + 1) * DE + cB] | ((uint32_t)wd[(4 * q + 3) * DE + cB] << 16);
        aup[0] = (uint32_t)wu[(4 * q + 0) * DE + cA] | ((uint32_t)wu[(4 * q + 2) * DE + cA] << 16);
        aup[1] = (uint32_t)wu[(4 * q + 0) * DE + cB] | ((uint32_t)wu[(4 * q + 2) * DE + cB] << 16);
        aup[2] = (uint32_t)wu[(4 * q + 1) * DE + cA] | ((uint32_t)wu[(4 * q + 3) * DE + cA] << 16);
        aup[3] = (uint32_t)wu[(4 * q + 1) * DE + cB] | ((uint32_t)wu[(4 * q + 3) * DE + cB] << 16);
#pragma unroll
        for (int l = 0; l < NL; l++) {
            asbf[l][0] = (uint32_t)ws[((2 * q) * NL + l) * DE + cA] | ((uint32_t)ws[((2 * q + 1) * NL + l) * DE + cA] << 16);
            asbf[l][1] = (uint32_t)ws[((2 * q) * NL + l) * DE + cB] | ((uint32_t)ws[((2 * q + 1) * NL + l) * DE + cB] << 16);
        }
        arb[0] = (uint32_t)wr[(2 * q) * DE + cA] | ((uint32_t)wr[(2 * q + 1) * DE + cA] << 16);
        arb[1] = (uint32_t)wr[(2 * q) * DE + cB] | ((uint32_t)wr[(2 * q + 1) * DE + cB] << 16);
    }
    const uint32_t cen = reinterpret_cast<const uint32_t*>(p.centers)[q];
    const unsigned char* mb = reinterpret_cast<const unsigned char*>(p.m);
    const unsigned short* dist16 = reinterpret_cast<const unsigned short*>(p.dist);
    const uint32_t g4 = 4u * g;
    const int sh = 7 - g;

#pragma unroll 1
    for (int grp = wid; grp < NGRP; grp += G_NT / 32) {
        const int s = gstart[grp], e = gstart[grp + 1];
        const int e0 = bin * NB + grp * 8;
        const int eg = e0 + g;
        const int ea = e0 + 2 * q;
        uint32_t dg = (eg < p.E) ? (uint32_t)dist16[eg] : 0u;
        const uint32_t moff = (uint32_t)ea * 32u + g4;
        uint32_t ma = (ea < p.E) ? __ldg(reinterpret_cast<const uint32_t*>(mb + moff)) : 0u;
        uint32_t mbv = (ea + 1 < p.E) ? __ldg(reinterpret_cast<const uint32_t*>(mb + moff + 32)) : 0u;

        float D[NL][4];
#pragma unroll
        for (int l = 0; l < NL; l++)
#pragma unroll
            for (int c = 0; c < 4; c++) D[l][c] = 0.f;
#pragma unroll 2
        for (int ch = (s >> 2) + q; ch < (e >> 2); ch += 4) {
            uint4 w = reinterpret_cast<const uint4*>(sidx)[ch];
            uint4 c01 = sc01[ch];
            uint2 c2 = reinterpret_cast<const uint2*>(sc2)[ch];
            uint32_t v0 = __ldg(reinterpret_cast<const uint32_t*>(mb + ((w.x & 0xffffffu) | g4)));
            uint32_t v1 = __ldg(reinterpret_cast<const uint32_t*>(mb + ((w.y & 0xffffffu) | g4)));
            uint32_t v2 = __ldg(reinterpret_cast<const uint32_t*>(mb + ((w.z & 0xffffffu) | g4)));
            uint32_t v3 = __ldg(reinterpret_cast<const uint32_t*>(mb + ((w.w & 0xffffffu) | g4)));
            uint32_t k01 = prmt(w.x << sh, w.y << sh, 0xFFBB);
            uint32_t k23 = prmt(w.z << sh, w.w << sh, 0xFFBB);
            uint32_t a[4];
            a[0] = prmt(v0, v1, 0x5410);
            a[1] = prmt(v0, v1, 0x7632);
            a[2] = prmt(v2, v3, 0x5410);
            a[3] = prmt(v2, v3, 0x7632);
            mma16816(D[0], a, c01.x & k01, c01.y & k23);
            mma16816(D[1], a, c01.z & k01, c01.w & k23);
            mma16816(D[2], a, c2.x & k01, c2.y & k23);
        }
        const uint32_t brbf = rbf_bf16x2(dg * 0x10001u, cen);
        float agg[4] = {0.f, 0.f, 0.f, 0.f};
#pragma unroll
        for (int l = 0; l < NL; l++) {
            uint32_t h0 = pack_bf16(D[l][0], D[l][1]);
            uint32_t h1 = pack_bf16(D[l][2], D[l][3]);
            uint32_t l0 = pack_bf16(D[l][0] - bf16lo(h0), D[l][1] - bf16hi(h0));
            uint32_t l1 = pack_bf16(D[l][2] - bf16lo(h1), D[l][3] - bf16hi(h1));
            h0 = movm(h0); h1 = movm(h1); l0 = movm(l0); l1 = movm(l1);
            float S[4] = {0.f, 0.f, 0.f, 0.f};
            float G[4] = {0.f, 0.f, 0.f, 0.f};
            mma16816(S, adown, l0, l1);
            mma16816(S, adown, h0, h1);
            mma1688(G, asbf[l], brbf);
#pragma unroll
            for (int c = 0; c < 4; c++) agg[c] = fmaf(S[c], G[c], agg[c]);
        }
        if (ovf) {
            if (ea < p.E) {
                float2* pa = reinterpret_cast<float2*>(g_ovf + (size_t)ea * DE + 2 * g);
                float2 o = __ldcg(pa); *pa = make_float2(0.f, 0.f);
                agg[0] += o.x; agg[2] += o.y;
            }
            if (ea + 1 < p.E) {
                float2* pb = reinterpret_cast<float2*>(g_ovf + (size_t)(ea + 1) * DE + 2 * g);
                float2 o = __ldcg(pb); *pb = make_float2(0.f, 0.f);
                agg[1] += o.x; agg[3] += o.y;
            }
        }
        {
            uint32_t h0 = pack_bf16(agg[0], agg[1]);
            uint32_t h1 = pack_bf16(agg[2], agg[3]);
            uint32_t l0 = pack_bf16(agg[0] - bf16lo(h0), agg[1] - bf16hi(h0));
            uint32_t l1 = pack_bf16(agg[2] - bf16lo(h1), agg[3] - bf16hi(h1));
            h0 = movm(h0); h1 = movm(h1); l0 = movm(l0); l1 = movm(l1);
            float U[4] = {0.f, 0.f, 0.f, 0.f};
            float R[4] = {0.f, 0.f, 0.f, 0.f};
            mma16816(U, aup, l0, l1);
            mma16816(U, aup, h0, h1);
            mma1688(R, arb, brbf);
            uint32_t oa = pack_bf16(fmaf(U[0], R[0], bf16lo(ma)), fmaf(U[2], R[2], bf16hi(ma)));
            uint32_t ob = pack_bf16(fmaf(U[1], R[1], bf16lo(mbv)), fmaf(U[3], R[3], bf16hi(mbv)));
            unsigned char* ob8 = reinterpret_cast<unsigned char*>(p.out);
            if (ea < p.E) *reinterpret_cast<uint32_t*>(ob8 + moff) = oa;
            if (ea + 1 < p.E) *reinterpret_cast<uint32_t*>(ob8 + moff + 32) = ob;
        }
    }
}

}

extern "C" void kernel_launch(void* const* d_in, const int* in_sizes, int n_in,
                              void* d_out, int out_size) {
    Params p;
    p.m = (const __nv_bfloat16*)d_in[0];
    p.idx_in = (const int*)d_in[1];
    p.idx_out = (const int*)d_in[2];
    p.dist = (const __nv_bfloat16*)d_in[3];
    p.angle = (const __nv_bfloat16*)d_in[4];
    p.centers = (const __nv_bfloat16*)d_in[5];
    p.ang_freq = (const __nv_bfloat16*)d_in[6];
    p.w_rbf = (const __nv_bfloat16*)d_in[7];
    p.w_sbf = (const __nv_bfloat16*)d_in[8];
    p.w_down = (const __nv_bfloat16*)d_in[9];
    p.w_up = (const __nv_bfloat16*)d_in[10];
    p.out = (__nv_bfloat16*)d_out;
    p.E = in_sizes[3];
    p.T = in_sizes[1];
    p.nbins = (p.E + NB - 1) / NB;
    p.ntiles = (p.T + P_TILE - 1) / P_TILE;

    const int smem1 = (P_TILE + 8) * 8 + (2 * BINS_PAD + 4) * 4;
    const int smem2 = (CAPS + 8) * 4 + CAPS * 4 + (CAPS + 8) * 2;
    static int nsm = 0;
    if (!nsm) {
        cudaFuncSetAttribute(k_partition, cudaFuncAttributeMaxDynamicSharedMemorySize, smem1);
        cudaFuncSetAttribute(k_gather, cudaFuncAttributeMaxDynamicSharedMemorySize, smem2);
        int dev = 0;
        cudaGetDevice(&dev);
        cudaDeviceGetAttribute(&nsm, cudaDevAttrMultiProcessorCount, dev);
    }
    int g1 = p.ntiles < nsm ? p.ntiles : nsm;
    k_partition<<<g1, P_NT, smem1>>>(p);
    k_gather<<<p.nbins, G_NT, smem2>>>(p);
}
```

```cpp
#include <cuda_runtime.h>
#include <cuda_bf16.h>
#include <stdint.h>

namespace {

constexpr int DE = 16;
constexpr int NR = 8;
constexpr int NL = 3;

constexpr int NB_LOG = 8;
constexpr int NB = 1 << NB_LOG;
constexpr int MAX_E = 400000;
constexpr int MAX_BINS = (MAX_E + NB - 1) / NB;
constexpr int BINS_PAD = 2048;
constexpr int CAPG = 5120;

constexpr int P_NT = 1024;
constexpr int P_PER = 16;
constexpr int P_TILE_MAX = P_NT * P_PER;
constexpr int P_STAGE = P_TILE_MAX + 3 * MAX_BINS + 16;

constexpr int G_NT = 256;
constexpr int G_PER = CAPG / G_NT;
constexpr int NGRP = NB / 8;
constexpr int CAPS = CAPG + NGRP * 16;
constexpr int G_STAGES = 3;

__device__ uint2 g_records[(size_t)MAX_BINS * CAPG];
__device__ int g_cursor[BINS_PAD];
__device__ float g_ovf[(size_t)MAX_BINS * NB * DE];

__device__ __forceinline__ float bf16r(float x) { return __bfloat162float(__float2bfloat16_rn(x)); }
__device__ __forceinline__ float bf16lo(uint32_t v) { return __uint_as_float(v << 16); }
__device__ __forceinline__ float bf16hi(uint32_t v) { return __uint_as_float(v & 0xffff0000u); }
__device__ __forceinline__ float ldbf(const __nv_bfloat16* p) { return __bfloat162float(*p); }
__device__ __forceinline__ uint32_t smem_u32(const void* p) { return (uint32_t)__cvta_generic_to_shared(p); }

__device__ __forceinline__ uint32_t pack_bf16(float lo, float hi) {
    __nv_bfloat162 v = __floats2bfloat162_rn(lo, hi);
    return *reinterpret_cast<uint32_t*>(&v);
}
__device__ __forceinline__ uint32_t mul_bf16x2(uint32_t a, uint32_t b) {
    __nv_bfloat162 r = __hmul2(*reinterpret_cast<__nv_bfloat162*>(&a), *reinterpret_cast<__nv_bfloat162*>(&b));
    return *reinterpret_cast<uint32_t*>(&r);
}
__device__ __forceinline__ uint32_t sub_bf16x2(uint32_t a, uint32_t b) {
    __nv_bfloat162 r = __hsub2(*reinterpret_cast<__nv_bfloat162*>(&a), *reinterpret_cast<__nv_bfloat162*>(&b));
    return *reinterpret_cast<uint32_t*>(&r);
}
__device__ __forceinline__ uint32_t cos_fast_bf16x2(uint32_t x) {
    return pack_bf16(__cosf(bf16lo(x)), __cosf(bf16hi(x)));
}
__device__ __noinline__ uint32_t cos_slow_bf16x2(uint32_t x) {
    return pack_bf16(cosf(bf16lo(x)), cosf(bf16hi(x)));
}
__device__ __forceinline__ uint32_t rbf_bf16x2(uint32_t dd, uint32_t cc) {
    uint32_t t = sub_bf16x2(dd, cc);
    t = mul_bf16x2(t, t);
    t = mul_bf16x2(t, 0xC120C120u);
    return pack_bf16(__expf(bf16lo(t)), __expf(bf16hi(t)));
}

__device__ __forceinline__ void mma16816(float* d, const uint32_t* a, uint32_t b0, uint32_t b1) {
    asm volatile("mma.sync.aligned.m16n8k16.row.col.f32.bf16.bf16.f32 {%0,%1,%2,%3}, {%4,%5,%6,%7}, {%8,%9}, {%0,%1,%2,%3};"
                 : "+f"(d[0]), "+f"(d[1]), "+f"(d[2]), "+f"(d[3])
                 : "r"(a[0]), "r"(a[1]), "r"(a[2]), "r"(a[3]), "r"(b0), "r"(b1));
}
__device__ __forceinline__ void mma1688(float* d, const uint32_t* a, uint32_t b) {
    asm volatile("mma.sync.aligned.m16n8k8.row.col.f32.bf16.bf16.f32 {%0,%1,%2,%3}, {%4,%5}, {%6}, {%0,%1,%2,%3};"
                 : "+f"(d[0]), "+f"(d[1]), "+f"(d[2]), "+f"(d[3])
                 : "r"(a[0]), "r"(a[1]), "r"(b));
}
__device__ __forceinline__ uint32_t movm(uint32_t a) {
    uint32_t d;
    asm volatile("movmatrix.sync.aligned.m8n8.trans.b16 %0, %1;" : "=r"(d) : "r"(a));
    return d;
}
__device__ __forceinline__ uint32_t prmt(uint32_t a, uint32_t b, uint32_t sel) {
    uint32_t d;
    asm("prmt.b32 %0, %1, %2, %3;" : "=r"(d) : "r"(a), "r"(b), "r"(sel));
    return d;
}
__device__ __forceinline__ void ldsm_x4_trans(uint32_t* r, uint32_t addr) {
    asm volatile("ldmatrix.sync.aligned.m8n8.x4.trans.shared.b16 {%0,%1,%2,%3}, [%4];"
                 : "=r"(r[0]), "=r"(r[1]), "=r"(r[2]), "=r"(r[3]) : "r"(addr) : "memory");
}
__device__ __forceinline__ void cp_async16(uint32_t dst, const void* src) {
    asm volatile("cp.async.cg.shared.global [%0], [%1], 16;" :: "r"(dst), "l"(src) : "memory");
}
__device__ __forceinline__ void cp_async_commit() { asm volatile("cp.async.commit_group;" ::: "memory"); }
template <int N> __device__ __forceinline__ void cp_async_wait() { asm volatile("cp.async.wait_group %0;" :: "n"(N) : "memory"); }

struct Params {
    const __nv_bfloat16* m;
    const int* idx_in;
    const int* idx_out;
    const __nv_bfloat16* dist;
    const __nv_bfloat16* angle;
    const __nv_bfloat16* centers;
    const __nv_bfloat16* ang_freq;
    const __nv_bfloat16* w_rbf;
    const __nv_bfloat16* w_sbf;
    const __nv_bfloat16* w_down;
    const __nv_bfloat16* w_up;
    __nv_bfloat16* out;
    int E, T, nbins, ntiles, tile;
};

__device__ __noinline__ void slow_bin(const Params* pp, int bin) {
    const Params& p = *pp;
    for (int t = threadIdx.x; t < p.T; t += blockDim.x) {
        const int out = p.idx_out[t];
        if ((out >> NB_LOG) != bin) continue;
        const int in = p.idx_in[t];
        const float ang = ldbf(p.angle + t);
        float mrow[DE], rb[NR], cb[NL];
        for (int k = 0; k < DE; k++) mrow[k] = ldbf(p.m + (size_t)in * DE + k);
        float d = ldbf(p.dist + out);
        for (int r = 0; r < NR; r++) {
            float u = bf16r(d - ldbf(p.centers + r));
            u = bf16r(u * u);
            u = bf16r(-10.0f * u);
            rb[r] = bf16r(__expf(u));
        }
        for (int l = 0; l < NL; l++) cb[l] = bf16r(cosf(bf16r(ldbf(p.ang_freq + l) * ang)));
        for (int c = 0; c < DE; c++) {
            float md = 0.f, s = 0.f;
            for (int k = 0; k < DE; k++) md = fmaf(mrow[k], ldbf(p.w_down + k * DE + c), md);
            for (int r = 0; r < NR; r++)
                for (int l = 0; l < NL; l++) s = fmaf(rb[r] * cb[l], ldbf(p.w_sbf + (r * NL + l) * DE + c), s);
            atomicAdd(&g_ovf[(size_t)out * DE + c], md * s);
        }
    }
    __threadfence();
}

__device__ __forceinline__ int4 ld4_guard(const int* p, int i, int n, int fill) {
    if (i + 3 < n) return __ldcs(reinterpret_cast<const int4*>(p + i));
    int4 r;
    r.x = (i + 0 < n) ? p[i + 0] : fill;
    r.y = (i + 1 < n) ? p[i + 1] : fill;
    r.z = (i + 2 < n) ? p[i + 2] : fill;
    r.w = fill;
    return r;
}
__device__ __forceinline__ uint2 ld4h_guard(const unsigned short* p, int i, int n) {
    if (i + 3 < n) return __ldcs(reinterpret_cast<const uint2*>(p + i));
    uint32_t a = (i + 0 < n) ? p[i + 0] : 0u, b = (i + 1 < n) ? p[i + 1] : 0u, c = (i + 2 < n) ? p[i + 2] : 0u;
    return make_uint2(a | (b << 16), c);
}

__global__ void __launch_bounds__(P_NT, 1) k_partition(const __grid_constant__ Params p) {
    extern __shared__ __align__(16) unsigned char smem_raw[];
    uint2* stage = reinterpret_cast<uint2*>(smem_raw);
    int* hist = reinterpret_cast<int*>(smem_raw + (size_t)P_STAGE * 8);
    __shared__ int warp_sums[P_NT / 32];
    static_assert(BINS_PAD == 2 * P_NT, "two bins per thread in the scan");

    const int tid = threadIdx.x;
    const int lane = tid & 31, wid = tid >> 5;
    const unsigned short* ang16 = reinterpret_cast<const unsigned short*>(p.angle);

    int4 O[P_PER / 4];
    int tile = blockIdx.x;
    if (tile < p.ntiles) {
        const int base = tile * p.tile, n = min(p.tile, p.T - base);
#pragma unroll
        for (int v = 0; v < P_PER / 4; v++) O[v] = ld4_guard(p.idx_out + base, (v * P_NT + tid) * 4, n, -1);
    }
    reinterpret_cast<int2*>(hist)[tid] = make_int2(0, 0);
    if (tid == 0) hist[BINS_PAD] = 0;
    for (; tile < p.ntiles; tile += gridDim.x) {
        const int base = tile * p.tile, n = min(p.tile, p.T - base);
        __syncthreads();
#pragma unroll
        for (int v = 0; v < P_PER / 4; v++) {
            atomicAdd(&hist[min((uint32_t)O[v].x >> NB_LOG, (uint32_t)BINS_PAD)], 1);
            atomicAdd(&hist[min((uint32_t)O[v].y >> NB_LOG, (uint32_t)BINS_PAD)], 1);
            atomicAdd(&hist[min((uint32_t)O[v].z >> NB_LOG, (uint32_t)BINS_PAD)], 1);
            atomicAdd(&hist[min((uint32_t)O[v].w >> NB_LOG, (uint32_t)BINS_PAD)], 1);
        }
        int4 I[P_PER / 4];
        uint2 A[P_PER / 4];
#pragma unroll
        for (int v = 0; v < P_PER / 4; v++) {
            I[v] = ld4_guard(p.idx_in + base, (v * P_NT + tid) * 4, n, 0);
            A[v] = ld4h_guard(ang16 + base, (v * P_NT + tid) * 4, n);
        }
        __syncthreads();
        const int2 c2 = reinterpret_cast<int2*>(hist)[tid];
        const int pc0 = (c2.x + 3) & ~3, pc1 = (c2.y + 3) & ~3;
        int g0 = 0, g1 = 0;
        if (pc0) g0 = atomicAdd(&g_cursor[2 * tid], pc0);
        if (pc1) g1 = atomicAdd(&g_cursor[2 * tid + 1], pc1);
        const int s = pc0 + pc1;
        int inc = s;
#pragma unroll
        for (int o = 1; o < 32; o <<= 1) {
            int t = __shfl_up_sync(0xffffffffu, inc, o);
            if (lane >= o) inc += t;
        }
        if (lane == 31) warp_sums[wid] = inc;
        asm volatile("cp.async.bulk.wait_group.read 0;" ::: "memory");
        __syncthreads();
        int woff;
        {
            int ws = warp_sums[lane];
            int winc = ws;
#pragma unroll
            for (int o = 1; o < 32; o <<= 1) {
                int t = __shfl_up_sync(0xffffffffu, winc, o);
                if (lane >= o) winc += t;
            }
            woff = __shfl_sync(0xffffffffu, winc - ws, wid);
        }
        const int e0 = woff + inc - s, e1 = e0 + pc0;
        reinterpret_cast<int2*>(hist)[tid] = make_int2(e0, e1);
        if (tid == 0) hist[BINS_PAD] = P_STAGE;
        for (int k = c2.x; k < pc0; k++) stage[e0 + k] = make_uint2(0u, 0xffffffffu);
        for (int k = c2.y; k < pc1; k++) stage[e1 + k] = make_uint2(0u, 0xffffffffu);
        __syncthreads();
#pragma unroll
        for (int v = 0; v < P_PER / 4; v++) {
            const uint32_t o[4] = {(uint32_t)O[v].x, (uint32_t)O[v].y, (uint32_t)O[v].z, (uint32_t)O[v].w};
            const uint32_t in[4] = {(uint32_t)I[v].x, (uint32_t)I[v].y, (uint32_t)I[v].z, (uint32_t)I[v].w};
            const uint32_t an[4] = {A[v].x & 0xffffu, A[v].x >> 16, A[v].y & 0xffffu, A[v].y >> 16};
#pragma unroll
            for (int u = 0; u < 4; u++) {
                int pos = atomicAdd(&hist[min(o[u] >> NB_LOG, (uint32_t)BINS_PAD)], 1);
                stage[min(pos, P_STAGE - 1)] = make_uint2((in[u] << 5) | (o[u] << 24), an[u]);
            }
        }
        {
            const int nt = tile + gridDim.x;
            if (nt < p.ntiles) {
                const int nbase = nt * p.tile, nn = min(p.tile, p.T - nbase);
#pragma unroll
                for (int v = 0; v < P_PER / 4; v++) O[v] = ld4_guard(p.idx_out + nbase, (v * P_NT + tid) * 4, nn, -1);
            }
        }
        asm volatile("fence.proxy.async.shared::cta;" ::: "memory");
        __syncthreads();
        if (pc0 && g0 + pc0 <= CAPG)
            asm volatile("cp.async.bulk.global.shared::cta.bulk_group [%0], [%1], %2;"
                         :: "l"(g_records + (size_t)(2 * tid) * CAPG + g0), "r"(smem_u32(stage + e0)), "r"(pc0 * 8) : "memory");
        if (pc1 && g1 + pc1 <= CAPG)
            asm volatile("cp.async.bulk.global.shared::cta.bulk_group [%0], [%1], %2;"
                         :: "l"(g_records + (size_t)(2 * tid + 1) * CAPG + g1), "r"(smem_u32(stage + e1)), "r"(pc1 * 8) : "memory");
        asm volatile("cp.async.bulk.commit_group;" ::: "memory");
        reinterpret_cast<int2*>(hist)[tid] = make_int2(0, 0);
        if (tid == 0) hist[BINS_PAD] = 0;
    }
    asm volatile("cp.async.bulk.wait_group 0;" ::: "memory");
}

constexpr int SM_IDX = 0;
constexpr int SM_C01 = SM_IDX + (CAPS + 16) * 4;
constexpr int SM_C2 = SM_C01 + CAPS * 4;
constexpr int SM_OH = SM_C2 + (CAPS + 16) * 2;
constexpr int SM_RING = SM_OH + CAPS;
constexpr int SM_TOTAL = SM_RING + (G_NT / 32) * G_STAGES * 512;

__global__ void __launch_bounds__(G_NT, 3) k_gather(const __grid_constant__ Params p) {
    extern __shared__ __align__(128) unsigned char smem_raw[];
    uint32_t* sidx = reinterpret_cast<uint32_t*>(smem_raw + SM_IDX);
    uint4* sc01 = reinterpret_cast<uint4*>(smem_raw + SM_C01);
    unsigned short* sc2 = reinterpret_cast<unsigned short*>(smem_raw + SM_C2);
    uint32_t* soh = reinterpret_cast<uint32_t*>(smem_raw + SM_OH);
    __shared__ int cnts[NB + 1];
    __shared__ int start[NB + 1];
    __shared__ int warp_sums[G_NT / 32];
    static_assert(NB == G_NT, "one edge per thread in the scan");

    const int tid = threadIdx.x;
    const int lane = tid & 31, wid = tid >> 5;
    const int bin = blockIdx.x;
    const int total = g_cursor[bin];
    const bool ovf = total > CAPG;
    const int n = ovf ? 0 : total;
    if (ovf) slow_bin(&p, bin);

    const uint2* rec = g_records + (size_t)bin * CAPG + tid;
    uint2 r[G_PER];
#pragma unroll
    for (int j = 0; j < G_PER; j++) {
        r[j] = make_uint2(0u, 0xffffffffu);
        if (j * G_NT + tid < n) r[j] = __ldcs(rec + j * G_NT);
    }
    cnts[tid] = 0;
    if (tid == 0) cnts[NB] = 0;
    for (int i = tid; i < CAPS / 4; i += G_NT) reinterpret_cast<uint4*>(sidx)[i] = make_uint4(0, 0, 0, 0);
    for (int i = tid; i < CAPS / 8; i += G_NT) reinterpret_cast<uint4*>(sc2)[i] = make_uint4(0, 0, 0, 0);
    const unsigned short* fq = reinterpret_cast<const unsigned short*>(p.ang_freq);
    const uint32_t f0 = (uint32_t)fq[0] * 0x10001u, f1 = (uint32_t)fq[1] * 0x10001u, f2 = (uint32_t)fq[2] * 0x10001u;
    const uint32_t fmaxp = max(max(f0 & 0x7fff7fffu, f1 & 0x7fff7fffu), f2 & 0x7fff7fffu);
    __syncthreads();
    if (tid == 0) g_cursor[bin] = 0;
#pragma unroll
    for (int j = 0; j < G_PER; j++) {
        const bool inval = r[j].y == 0xffffffffu;
        uint32_t rk = (uint32_t)atomicAdd(&cnts[inval ? (uint32_t)NB : (r[j].x >> 24)], 1);
        r[j].y = inval ? 0xffff0000u : (r[j].y | (rk << 16));
    }
    __syncthreads();
    {
        const int c = cnts[tid];
        int gt = c;
        gt += __shfl_xor_sync(0xffffffffu, gt, 1);
        gt += __shfl_xor_sync(0xffffffffu, gt, 2);
        gt += __shfl_xor_sync(0xffffffffu, gt, 4);
        const int cp = c + (((lane & 7) == 7) ? (((gt + 15) & ~15) - gt) : 0);
        int inc = cp;
#pragma unroll
        for (int o = 1; o < 32; o <<= 1) {
            int t = __shfl_up_sync(0xffffffffu, inc, o);
            if (lane >= o) inc += t;
        }
        if (lane == 31) warp_sums[wid] = inc;
        __syncthreads();
        int woff = 0;
#pragma unroll
        for (int w = 0; w < G_NT / 32; w++) woff += (w < wid) ? warp_sums[w] : 0;
        start[tid] = woff + inc - cp;
        if (tid == G_NT - 1) start[NB] = woff + inc;
    }
    __syncthreads();
#pragma unroll
    for (int j = 0; j < G_PER; j++) {
        const uint32_t le = r[j].x >> 24;
        const uint32_t pos = min((uint32_t)start[le] + (r[j].y >> 16), (uint32_t)CAPS);
        sidx[pos] = (r[j].x & 0xffffffu) | (0x1000000u << (le & 7));
        sc2[pos] = (unsigned short)(r[j].y);
    }
    __syncthreads();
    {
        const int nch = start[NB] >> 2;
        for (int i = tid; i < nch; i += G_NT) {
            const uint2 a = reinterpret_cast<const uint2*>(sc2)[i];
            const uint4 w = reinterpret_cast<const uint4*>(sidx)[i];
            soh[i] = prmt(prmt(w.x, w.y, 0x0073), prmt(w.z, w.w, 0x0073), 0x5410);
            uint32_t x0 = mul_bf16x2(a.x, f0), x1 = mul_bf16x2(a.y, f0);
            uint32_t x2 = mul_bf16x2(a.x, f1), x3 = mul_bf16x2(a.y, f1);
            uint32_t x4 = mul_bf16x2(a.x, f2), x5 = mul_bf16x2(a.y, f2);
            uint32_t t = mul_bf16x2(__vmaxu2(a.x & 0x7fff7fffu, a.y & 0x7fff7fffu), fmaxp);
            uint4 o; uint2 o2;
            if ((t >> 16) < 0x4300u && (t & 0xffffu) < 0x4300u) {
                o.x = cos_fast_bf16x2(x0); o.y = cos_fast_bf16x2(x1);
                o.z = cos_fast_bf16x2(x2); o.w = cos_fast_bf16x2(x3);
                o2.x = cos_fast_bf16x2(x4); o2.y = cos_fast_bf16x2(x5);
            } else {
                o.x = cos_slow_bf16x2(x0); o.y = cos_slow_bf16x2(x1);
                o.z = cos_slow_bf16x2(x2); o.w = cos_slow_bf16x2(x3);
                o2.x = cos_slow_bf16x2(x4); o2.y = cos_slow_bf16x2(x5);
            }
            sc01[i] = o;
            reinterpret_cast<uint2*>(sc2)[i] = o2;
        }
    }
    __syncthreads();

    const int g = lane >> 2, q = lane & 3;
    constexpr int GPW = NGRP / (G_NT / 32);
    const int grp0 = wid * GPW;
    const int wend = start[(grp0 + GPW) * 8];
    const unsigned char* mb = reinterpret_cast<const unsigned char*>(p.m);

    const uint32_t ring = smem_u32(smem_raw + SM_RING) + wid * (G_STAGES * 512);
    const int cj = lane >> 1;
    const uint32_t cdst = (uint32_t)((lane & 1) * 256 + (((cj >> 2) * 2 + (cj & 1) + ((cj >> 1) & 1) * 8) * 16));
    const unsigned char* msrc = mb + (lane & 1) * 16;
    const uint32_t lsrc = (uint32_t)(((lane >> 3) & 1) * 256 + ((lane >> 4) * 8 + (lane & 7)) * 16);

    int ipos = start[grp0 * 8];
    int islot = 0;
#pragma unroll
    for (int k = 0; k < G_STAGES - 1; k++) {
        if (ipos < wend) cp_async16(ring + islot * 512 + cdst, msrc + (sidx[ipos + cj] & 0xffffffu));
        cp_async_commit();
        ipos += 16; islot++;
    }

    uint32_t adown[4], aup[4], asbf[NL][2], arb[2];
    {
        const unsigned short* wd = reinterpret_cast<const unsigned short*>(p.w_down);
        const unsigned short* wu = reinterpret_cast<const unsigned short*>(p.w_up);
        const unsigned short* ws = reinterpret_cast<const unsigned short*>(p.w_sbf);
        const unsigned short* wr = reinterpret_cast<const unsigned short*>(p.w_rbf);
        adown[0] = (uint32_t)wd[(2 * q) * DE + g] | ((uint32_t)wd[(2 * q + 1) * DE + g] << 16);
        adown[1] = (uint32_t)wd[(2 * q) * DE + g + 8] | ((uint32_t)wd[(2 * q + 1) * DE + g + 8] << 16);
        adown[2] = (uint32_t)wd[(2 * q + 8) * DE + g] | ((uint32_t)wd[(2 * q + 9) * DE + g] << 16);
        adown[3] = (uint32_t)wd[(2 * q + 8) * DE + g + 8] | ((uint32_t)wd[(2 * q + 9) * DE + g + 8] << 16);
#pragma unroll
        for (int l = 0; l < NL; l++) {
            asbf[l][0] = (uint32_t)ws[((2 * q) * NL + l) * DE + g] | ((uint32_t)ws[((2 * q + 1) * NL + l) * DE + g] << 16);
            asbf[l][1] = (uint32_t)ws[((2 * q) * NL + l) * DE + g + 8] | ((uint32_t)ws[((2 * q + 1) * NL + l) * DE + g + 8] << 16);
        }
        const int cA = 2 * g, cB = 2 * g + 1;
        aup[0] = (uint32_t)wu[(2 * q) * DE + cA] | ((uint32_t)wu[(2 * q + 1) * DE + cA] << 16);
        aup[1] = (uint32_t)wu[(2 * q) * DE + cB] | ((uint32_t)wu[(2 * q + 1) * DE + cB] << 16);
        aup[2] = (uint32_t)wu[(2 * q + 8) * DE + cA] | ((uint32_t)wu[(2 * q + 9) * DE + cA] << 16);
        aup[3] = (uint32_t)wu[(2 * q + 8) * DE + cB] | ((uint32_t)wu[(2 * q + 9) * DE + cB] << 16);
        arb[0] = (uint32_t)wr[(2 * q) * DE + cA] | ((uint32_t)wr[(2 * q + 1) * DE + cA] << 16);
        arb[1] = (uint32_t)wr[(2 * q) * DE + cB] | ((uint32_t)wr[(2 * q + 1) * DE + cB] << 16);
    }
    const uint32_t cen = reinterpret_cast<const uint32_t*>(p.centers)[q];
    const unsigned short* dist16 = reinterpret_cast<const unsigned short*>(p.dist);

    int pos = start[grp0 * 8];
    int cslot = 0;
#pragma unroll 1
    for (int gi = 0; gi < GPW; gi++) {
        const int grp = grp0 + gi;
        const int e = start[(grp + 1) * 8];
        const int e0 = bin * NB + grp * 8;
        const int eg = e0 + g;
        const int ea = e0 + 2 * q;
        uint32_t dg = (eg < p.E) ? (uint32_t)dist16[eg] : 0u;
        const uint32_t moff = (uint32_t)ea * 32u + 4u * g;
        uint32_t ma = (ea < p.E) ? __ldg(reinterpret_cast<const uint32_t*>(mb + moff)) : 0u;
        uint32_t mbv = (ea + 1 < p.E) ? __ldg(reinterpret_cast<const uint32_t*>(mb + moff + 32)) : 0u;

        float D[NL][4];
#pragma unroll
        for (int l = 0; l < NL; l++)
#pragma unroll
            for (int c = 0; c < 4; c++) D[l][c] = 0.f;
#pragma unroll 1
        for (; pos < e; pos += 16) {
            if (ipos < wend) cp_async16(ring + islot * 512 + cdst, msrc + (sidx[ipos + cj] & 0xffffffu));
            cp_async_commit();
            ipos += 16; islot = (islot == G_STAGES - 1) ? 0 : islot + 1;
            const int ch = (pos >> 2) + q;
            const uint4 c01 = sc01[ch];
            const uint2 c2 = reinterpret_cast<const uint2*>(sc2)[ch];
            const uint32_t kb = ((soh[ch] >> g) & 0x01010101u) * 0xffu;
            const uint32_t k01 = prmt(kb, 0, 0x1100), k23 = prmt(kb, 0, 0x3322);
            cp_async_wait<G_STAGES - 1>();
            __syncwarp();
            uint32_t a[4];
            ldsm_x4_trans(a, ring + cslot * 512 + lsrc);
            cslot = (cslot == G_STAGES - 1) ? 0 : cslot + 1;
            mma16816(D[0], a, c01.x & k01, c01.y & k23);
            mma16816(D[1], a, c01.z & k01, c01.w & k23);
            mma16816(D[2], a, c2.x & k01, c2.y & k23);
        }
        const uint32_t brbf = rbf_bf16x2(dg * 0x10001u, cen);
        float agg[4] = {0.f, 0.f, 0.f, 0.f};
#pragma unroll
        for (int l = 0; l < NL; l++) {
            uint32_t h0 = pack_bf16(D[l][0], D[l][1]);
            uint32_t h1 = pack_bf16(D[l][2], D[l][3]);
            uint32_t l0 = pack_bf16(D[l][0] - bf16lo(h0), D[l][1] - bf16hi(h0));
            uint32_t l1 = pack_bf16(D[l][2] - bf16lo(h1), D[l][3] - bf16hi(h1));
            h0 = movm(h0); h1 = movm(h1); l0 = movm(l0); l1 = movm(l1);
            float S[4] = {0.f, 0.f, 0.f, 0.f};
            float G[4] = {0.f, 0.f, 0.f, 0.f};
            mma16816(S, adown, l0, l1);
            mma16816(S, adown, h0, h1);
            mma1688(G, asbf[l], brbf);
#pragma unroll
            for (int c = 0; c < 4; c++) agg[c] = fmaf(S[c], G[c], agg[c]);
        }
        if (ovf) {
            if (ea < p.E) {
                float* pa = g_ovf + (size_t)ea * DE + g;
                agg[0] += __ldcg(pa); agg[2] += __ldcg(pa + 8);
                pa[0] = 0.f; pa[8] = 0.f;
            }
            if (ea + 1 < p.E) {
                float* pb = g_ovf + (size_t)(ea + 1) * DE + g;
                agg[1] += __ldcg(pb); agg[3] += __ldcg(pb + 8);
                pb[0] = 0.f; pb[8] = 0.f;
            }
        }
        {
            uint32_t h0 = pack_bf16(agg[0], agg[1]);
            uint32_t h1 = pack_bf16(agg[2], agg[3]);
            uint32_t l0 = pack_bf16(agg[0] - bf16lo(h0), agg[1] - bf16hi(h0));
            uint32_t l1 = pack_bf16(agg[2] - bf16lo(h1), agg[3] - bf16hi(h1));
            h0 = movm(h0); h1 = movm(h1); l0 = movm(l0); l1 = movm(l1);
            float U[4] = {0.f, 0.f, 0.f, 0.f};
            float R[4] = {0.f, 0.f, 0.f, 0.f};
            mma16816(U, aup, l0, l1);
            mma16816(U, aup, h0, h1);
            mma1688(R, arb, brbf);
            uint32_t oa = pack_bf16(fmaf(U[0], R[0], bf16lo(ma)), fmaf(U[2], R[2], bf16hi(ma)));
            uint32_t ob = pack_bf16(fmaf(U[1], R[1], bf16lo(mbv)), fmaf(U[3], R[3], bf16hi(mbv)));
            unsigned char* ob8 = reinterpret_cast<unsigned char*>(p.out);
            if (ea < p.E) *reinterpret_cast<uint32_t*>(ob8 + moff) = oa;
            if (ea + 1 < p.E) *reinterpret_cast<uint32_t*>(ob8 + moff + 32) = ob;
        }
    }
}

}

extern "C" void kernel_launch(void* const* d_in, const int* in_sizes, int n_in,
                              void* d_out, int out_size) {
    Params p;
    p.m = (const __nv_bfloat16*)d_in[0];
    p.idx_in = (const int*)d_in[1];
    p.idx_out = (const int*)d_in[2];
    p.dist = (const __nv_bfloat16*)d_in[3];
    p.angle = (const __nv_bfloat16*)d_in[4];
    p.centers = (const __nv_bfloat16*)d_in[5];
    p.ang_freq = (const __nv_bfloat16*)d_in[6];
    p.w_rbf = (const __nv_bfloat16*)d_in[7];
    p.w_sbf = (const __nv_bfloat16*)d_in[8];
    p.w_down = (const __nv_bfloat16*)d_in[9];
    p.w_up = (const __nv_bfloat16*)d_in[10];
    p.out = (__nv_bfloat16*)d_out;
    p.E = in_sizes[3];
    p.T = in_sizes[1];
    p.nbins = (p.E + NB - 1) / NB;

    const int smem1 = P_STAGE * 8 + (BINS_PAD + 4) * 4;
    const int smem2 = SM_TOTAL;
    static int nsm = 0;
    if (!nsm) {
        cudaFuncSetAttribute(k_partition, cudaFuncAttributeMaxDynamicSharedMemorySize, smem1);
        cudaFuncSetAttribute(k_gather, cudaFuncAttributeMaxDynamicSharedMemorySize, smem2);
        int dev = 0;
        cudaGetDevice(&dev);
        cudaDeviceGetAttribute(&nsm, cudaDevAttrMultiProcessorCount, dev);
    }
    long long per_sm = ((long long)p.T + nsm - 1) / nsm;
    int k = (int)((per_sm + P_TILE_MAX - 1) / P_TILE_MAX);
    if (k < 1) k = 1;
    long long tile = ((long long)p.T + (long long)k * nsm - 1) / ((long long)k * nsm);
    tile = (tile + 15) & ~15LL;
    if (tile > P_TILE_MAX) tile = P_TILE_MAX;
    if (tile < 16) tile = 16;
    p.tile = (int)tile;
    p.ntiles = (int)(((long long)p.T + tile - 1) / tile);
    int g1 = p.ntiles < nsm ? p.ntiles : nsm;
    if (g1 > 0) k_partition<<<g1, P_NT, smem1>>>(p);
    k_gather<<<p.nbins, G_NT, smem2>>>(p);
}
```

```cpp
#include <cuda_runtime.h>
#include <cuda_bf16.h>
#include <stdint.h>

namespace {

constexpr int DE = 16;
constexpr int NR = 8;
constexpr int NL = 3;

constexpr int NB_LOG = 8;
constexpr int NB = 1 << NB_LOG;
constexpr int MAX_E = 400000;
constexpr int MAX_BINS = (MAX_E + NB - 1) / NB;
constexpr int BINS_PAD = 2048;
constexpr int CAPG = 5120;

constexpr int P_NT = 1024;
constexpr int P_PER = 16;
constexpr int P_TILE_MAX = P_NT * P_PER;
constexpr int P_STAGE = P_TILE_MAX + 3 * MAX_BINS + 16;

constexpr int G_NT = 256;
constexpr int G_PER = CAPG / G_NT;
constexpr int NGRP = NB / 8;
constexpr int CAPS = CAPG + NGRP * 16;
constexpr int G_STAGES = 3;

__device__ uint2 g_records[(size_t)MAX_BINS * CAPG];
__device__ int g_cursor[BINS_PAD];
__device__ float g_ovf[(size_t)MAX_BINS * NB * DE];

__device__ __forceinline__ float bf16r(float x) { return __bfloat162float(__float2bfloat16_rn(x)); }
__device__ __forceinline__ float bf16lo(uint32_t v) { return __uint_as_float(v << 16); }
__device__ __forceinline__ float bf16hi(uint32_t v) { return __uint_as_float(v & 0xffff0000u); }
__device__ __forceinline__ float ldbf(const __nv_bfloat16* p) { return __bfloat162float(*p); }
__device__ __forceinline__ uint32_t smem_u32(const void* p) { return (uint32_t)__cvta_generic_to_shared(p); }

__device__ __forceinline__ uint32_t pack_bf16(float lo, float hi) {
    __nv_bfloat162 v = __floats2bfloat162_rn(lo, hi);
    return *reinterpret_cast<uint32_t*>(&v);
}
__device__ __forceinline__ uint32_t mul_bf16x2(uint32_t a, uint32_t b) {
    __nv_bfloat162 r = __hmul2(*reinterpret_cast<__nv_bfloat162*>(&a), *reinterpret_cast<__nv_bfloat162*>(&b));
    return *reinterpret_cast<uint32_t*>(&r);
}
__device__ __forceinline__ uint32_t sub_bf16x2(uint32_t a, uint32_t b) {
    __nv_bfloat162 r = __hsub2(*reinterpret_cast<__nv_bfloat162*>(&a), *reinterpret_cast<__nv_bfloat162*>(&b));
    return *reinterpret_cast<uint32_t*>(&r);
}
__device__ __forceinline__ uint32_t cos_fast_bf16x2(uint32_t x) {
    return pack_bf16(__cosf(bf16lo(x)), __cosf(bf16hi(x)));
}
__device__ __noinline__ uint32_t cos_slow_bf16x2(uint32_t x) {
    return pack_bf16(cosf(bf16lo(x)), cosf(bf16hi(x)));
}
__device__ __forceinline__ uint32_t rbf_bf16x2(uint32_t dd, uint32_t cc) {
    uint32_t t = sub_bf16x2(dd, cc);
    t = mul_bf16x2(t, t);
    t = mul_bf16x2(t, 0xC120C120u);
    return pack_bf16(__expf(bf16lo(t)), __expf(bf16hi(t)));
}

__device__ __forceinline__ void mma16816(float* d, const uint32_t* a, uint32_t b0, uint32_t b1) {
    asm volatile("mma.sync.aligned.m16n8k16.row.col.f32.bf16.bf16.f32 {%0,%1,%2,%3}, {%4,%5,%6,%7}, {%8,%9}, {%0,%1,%2,%3};"
                 : "+f"(d[0]), "+f"(d[1]), "+f"(d[2]), "+f"(d[3])
                 : "r"(a[0]), "r"(a[1]), "r"(a[2]), "r"(a[3]), "r"(b0), "r"(b1));
}
__device__ __forceinline__ void mma1688(float* d, const uint32_t* a, uint32_t b) {
    asm volatile("mma.sync.aligned.m16n8k8.row.col.f32.bf16.bf16.f32 {%0,%1,%2,%3}, {%4,%5}, {%6}, {%0,%1,%2,%3};"
                 : "+f"(d[0]), "+f"(d[1]), "+f"(d[2]), "+f"(d[3])
                 : "r"(a[0]), "r"(a[1]), "r"(b));
}
__device__ __forceinline__ uint32_t movm(uint32_t a) {
    uint32_t d;
    asm volatile("movmatrix.sync.aligned.m8n8.trans.b16 %0, %1;" : "=r"(d) : "r"(a));
    return d;
}
__device__ __forceinline__ uint32_t prmt(uint32_t a, uint32_t b, uint32_t sel) {
    uint32_t d;
    asm("prmt.b32 %0, %1, %2, %3;" : "=r"(d) : "r"(a), "r"(b), "r"(sel));
    return d;
}
__device__ __forceinline__ void ldsm_x4_trans(uint32_t* r, uint32_t addr) {
    asm volatile("ldmatrix.sync.aligned.m8n8.x4.trans.shared.b16 {%0,%1,%2,%3}, [%4];"
                 : "=r"(r[0]), "=r"(r[1]), "=r"(r[2]), "=r"(r[3]) : "r"(addr) : "memory");
}
__device__ __forceinline__ void cp_async_row(uint32_t dst, const unsigned char* base, uint32_t w) {
    const uint32_t sz = (w >> 24) ? 16u : 0u;
    asm volatile("cp.async.cg.shared.global [%0], [%1], 16, %2;" :: "r"(dst), "l"(base + (w & 0xffffffu)), "r"(sz) : "memory");
}
__device__ __forceinline__ void cp_async_commit() { asm volatile("cp.async.commit_group;" ::: "memory"); }
template <int N> __device__ __forceinline__ void cp_async_wait() { asm volatile("cp.async.wait_group %0;" :: "n"(N) : "memory"); }

struct Params {
    const __nv_bfloat16* m;
    const int* idx_in;
    const int* idx_out;
    const __nv_bfloat16* dist;
    const __nv_bfloat16* angle;
    const __nv_bfloat16* centers;
    const __nv_bfloat16* ang_freq;
    const __nv_bfloat16* w_rbf;
    const __nv_bfloat16* w_sbf;
    const __nv_bfloat16* w_down;
    const __nv_bfloat16* w_up;
    __nv_bfloat16* out;
    int E, T, nbins, ntiles, tile;
};

__device__ __noinline__ void slow_bin(const Params* pp, int bin) {
    const Params& p = *pp;
    for (int t = threadIdx.x; t < p.T; t += blockDim.x) {
        const int out = p.idx_out[t];
        if ((out >> NB_LOG) != bin) continue;
        const int in = p.idx_in[t];
        const float ang = ldbf(p.angle + t);
        float mrow[DE], rb[NR], cb[NL];
        for (int k = 0; k < DE; k++) mrow[k] = ldbf(p.m + (size_t)in * DE + k);
        float d = ldbf(p.dist + out);
        for (int r = 0; r < NR; r++) {
            float u = bf16r(d - ldbf(p.centers + r));
            u = bf16r(u * u);
            u = bf16r(-10.0f * u);
            rb[r] = bf16r(__expf(u));
        }
        for (int l = 0; l < NL; l++) cb[l] = bf16r(cosf(bf16r(ldbf(p.ang_freq + l) * ang)));
        for (int c = 0; c < DE; c++) {
            float md = 0.f, s = 0.f;
            for (int k = 0; k < DE; k++) md = fmaf(mrow[k], ldbf(p.w_down + k * DE + c), md);
            for (int r = 0; r < NR; r++)
                for (int l = 0; l < NL; l++) s = fmaf(rb[r] * cb[l], ldbf(p.w_sbf + (r * NL + l) * DE + c), s);
            atomicAdd(&g_ovf[(size_t)out * DE + c], md * s);
        }
    }
    __threadfence();
}

__device__ __forceinline__ int4 ld4_guard(const int* p, int i, int n, int fill) {
    if (i + 3 < n) return __ldcs(reinterpret_cast<const int4*>(p + i));
    int4 r;
    r.x = (i + 0 < n) ? p[i + 0] : fill;
    r.y = (i + 1 < n) ? p[i + 1] : fill;
    r.z = (i + 2 < n) ? p[i + 2] : fill;
    r.w = fill;
    return r;
}
__device__ __forceinline__ uint2 ld4h_guard(const unsigned short* p, int i, int n) {
    if (i + 3 < n) return __ldcs(reinterpret_cast<const uint2*>(p + i));
    uint32_t a = (i + 0 < n) ? p[i + 0] : 0u, b = (i + 1 < n) ? p[i + 1] : 0u, c = (i + 2 < n) ? p[i + 2] : 0u;
    return make_uint2(a | (b << 16), c);
}

__global__ void __launch_bounds__(P_NT, 1) k_partition(const __grid_constant__ Params p) {
    extern __shared__ __align__(16) unsigned char smem_raw[];
    uint2* stage = reinterpret_cast<uint2*>(smem_raw);
    int* hist = reinterpret_cast<int*>(smem_raw + (size_t)P_STAGE * 8);
    __shared__ int warp_sums[P_NT / 32];
    static_assert(BINS_PAD == 2 * P_NT, "two bins per thread in the scan");

    const int tid = threadIdx.x;
    const int lane = tid & 31, wid = tid >> 5;
    const unsigned short* ang16 = reinterpret_cast<const unsigned short*>(p.angle);

    int4 O[P_PER / 4];
    int tile = blockIdx.x;
    if (tile < p.ntiles) {
        const int base = tile * p.tile, n = min(p.tile, p.T - base);
#pragma unroll
        for (int v = 0; v < P_PER / 4; v++) O[v] = ld4_guard(p.idx_out + base, (v * P_NT + tid) * 4, n, -1);
    }
    reinterpret_cast<int2*>(hist)[tid] = make_int2(0, 0);
    if (tid == 0) hist[BINS_PAD] = 0;
    for (; tile < p.ntiles; tile += gridDim.x) {
        const int base = tile * p.tile, n = min(p.tile, p.T - base);
        __syncthreads();
#pragma unroll
        for (int v = 0; v < P_PER / 4; v++) {
            atomicAdd(&hist[min((uint32_t)O[v].x >> NB_LOG, (uint32_t)BINS_PAD)], 1);
            atomicAdd(&hist[min((uint32_t)O[v].y >> NB_LOG, (uint32_t)BINS_PAD)], 1);
            atomicAdd(&hist[min((uint32_t)O[v].z >> NB_LOG, (uint32_t)BINS_PAD)], 1);
            atomicAdd(&hist[min((uint32_t)O[v].w >> NB_LOG, (uint32_t)BINS_PAD)], 1);
        }
        int4 I[P_PER / 4];
        uint2 A[P_PER / 4];
#pragma unroll
        for (int v = 0; v < P_PER / 4; v++) {
            I[v] = ld4_guard(p.idx_in + base, (v * P_NT + tid) * 4, n, 0);
            A[v] = ld4h_guard(ang16 + base, (v * P_NT + tid) * 4, n);
        }
        __syncthreads();
        const int2 c2 = reinterpret_cast<int2*>(hist)[tid];
        const int pc0 = (c2.x + 3) & ~3, pc1 = (c2.y + 3) & ~3;
        int g0 = 0, g1 = 0;
        if (pc0) g0 = atomicAdd(&g_cursor[2 * tid], pc0);
        if (pc1) g1 = atomicAdd(&g_cursor[2 * tid + 1], pc1);
        const int s = pc0 + pc1;
        int inc = s;
#pragma unroll
        for (int o = 1; o < 32; o <<= 1) {
            int t = __shfl_up_sync(0xffffffffu, inc, o);
            if (lane >= o) inc += t;
        }
        if (lane == 31) warp_sums[wid] = inc;
        asm volatile("cp.async.bulk.wait_group.read 0;" ::: "memory");
        __syncthreads();
        int woff;
        {
            int ws = warp_sums[lane];
            int winc = ws;
#pragma unroll
            for (int o = 1; o < 32; o <<= 1) {
                int t = __shfl_up_sync(0xffffffffu, winc, o);
                if (lane >= o) winc += t;
            }
            woff = __shfl_sync(0xffffffffu, winc - ws, wid);
        }
        const int e0 = woff + inc - s, e1 = e0 + pc0;
        reinterpret_cast<int2*>(hist)[tid] = make_int2(e0, e1);
        if (tid == 0) hist[BINS_PAD] = P_STAGE;
        for (int k = c2.x; k < pc0; k++) stage[e0 + k] = make_uint2(0u, 0xffffffffu);
        for (int k = c2.y; k < pc1; k++) stage[e1 + k] = make_uint2(0u, 0xffffffffu);
        __syncthreads();
#pragma unroll
        for (int v = 0; v < P_PER / 4; v++) {
            const uint32_t o[4] = {(uint32_t)O[v].x, (uint32_t)O[v].y, (uint32_t)O[v].z, (uint32_t)O[v].w};
            const uint32_t in[4] = {(uint32_t)I[v].x, (uint32_t)I[v].y, (uint32_t)I[v].z, (uint32_t)I[v].w};
            const uint32_t an[4] = {A[v].x & 0xffffu, A[v].x >> 16, A[v].y & 0xffffu, A[v].y >> 16};
#pragma unroll
            for (int u = 0; u < 4; u++) {
                int pos = atomicAdd(&hist[min(o[u] >> NB_LOG, (uint32_t)BINS_PAD)], 1);
                stage[min(pos, P_STAGE - 1)] = make_uint2((in[u] << 5) | (o[u] << 24), an[u]);
            }
        }
        {
            const int nt = tile + gridDim.x;
            if (nt < p.ntiles) {
                const int nbase = nt * p.tile, nn = min(p.tile, p.T - nbase);
#pragma unroll
                for (int v = 0; v < P_PER / 4; v++) O[v] = ld4_guard(p.idx_out + nbase, (v * P_NT + tid) * 4, nn, -1);
            }
        }
        asm volatile("fence.proxy.async.shared::cta;" ::: "memory");
        __syncthreads();
        if (pc0 && g0 + pc0 <= CAPG)
            asm volatile("cp.async.bulk.global.shared::cta.bulk_group [%0], [%1], %2;"
                         :: "l"(g_records + (size_t)(2 * tid) * CAPG + g0), "r"(smem_u32(stage + e0)), "r"(pc0 * 8) : "memory");
        if (pc1 && g1 + pc1 <= CAPG)
            asm volatile("cp.async.bulk.global.shared::cta.bulk_group [%0], [%1], %2;"
                         :: "l"(g_records + (size_t)(2 * tid + 1) * CAPG + g1), "r"(smem_u32(stage + e1)), "r"(pc1 * 8) : "memory");
        asm volatile("cp.async.bulk.commit_group;" ::: "memory");
        reinterpret_cast<int2*>(hist)[tid] = make_int2(0, 0);
        if (tid == 0) hist[BINS_PAD] = 0;
    }
    asm volatile("cp.async.bulk.wait_group 0;" ::: "memory");
}

constexpr int SM_IDX = 0;
constexpr int SM_C01 = SM_IDX + (CAPS + 16) * 4;
constexpr int SM_C2 = SM_C01 + CAPS * 4;
constexpr int SM_OH = SM_C2 + (CAPS + 16) * 2;
constexpr int SM_RING = SM_OH + CAPS;
constexpr int SM_TOTAL = SM_RING + (G_NT / 32) * G_STAGES * 512;

__global__ void __launch_bounds__(G_NT, 3) k_gather(const __grid_constant__ Params p) {
    extern __shared__ __align__(128) unsigned char smem_raw[];
    uint32_t* sidx = reinterpret_cast<uint32_t*>(smem_raw + SM_IDX);
    uint4* sc01 = reinterpret_cast<uint4*>(smem_raw + SM_C01);
    unsigned short* sc2 = reinterpret_cast<unsigned short*>(smem_raw + SM_C2);
    uint32_t* soh = reinterpret_cast<uint32_t*>(smem_raw + SM_OH);
    __shared__ int cnts[NB + 1];
    __shared__ int start[NB + 1];
    __shared__ int warp_sums[G_NT / 32];
    static_assert(NB == G_NT, "one edge per thread in the scan");

    const int tid = threadIdx.x;
    const int lane = tid & 31, wid = tid >> 5;
    const int bin = blockIdx.x;
    const int total = g_cursor[bin];
    const bool ovf = total > CAPG;
    const int n = ovf ? 0 : total;
    if (ovf) slow_bin(&p, bin);

    const uint2* rec = g_records + (size_t)bin * CAPG + tid;
    uint2 r[G_PER];
#pragma unroll
    for (int j = 0; j < G_PER; j++) {
        r[j] = make_uint2(0u, 0xffffffffu);
        if (j * G_NT + tid < n) r[j] = __ldcs(rec + j * G_NT);
    }
    cnts[tid] = 0;
    if (tid == 0) cnts[NB] = 0;
    for (int i = tid; i < CAPS / 4; i += G_NT) reinterpret_cast<uint4*>(sidx)[i] = make_uint4(0, 0, 0, 0);
    for (int i = tid; i < CAPS / 8; i += G_NT) reinterpret_cast<uint4*>(sc2)[i] = make_uint4(0, 0, 0, 0);
    const unsigned short* fq = reinterpret_cast<const unsigned short*>(p.ang_freq);
    const uint32_t f0 = (uint32_t)fq[0] * 0x10001u, f1 = (uint32_t)fq[1] * 0x10001u, f2 = (uint32_t)fq[2] * 0x10001u;
    const uint32_t fmaxp = max(max(f0 & 0x7fff7fffu, f1 & 0x7fff7fffu), f2 & 0x7fff7fffu);
    __syncthreads();
    if (tid == 0) g_cursor[bin] = 0;
#pragma unroll
    for (int j = 0; j < G_PER; j++) {
        const bool inval = r[j].y == 0xffffffffu;
        uint32_t rk = (uint32_t)atomicAdd(&cnts[inval ? (uint32_t)NB : (r[j].x >> 24)], 1);
        r[j].y = inval ? 0xffff0000u : (r[j].y | (rk << 16));
    }
    __syncthreads();
    {
        const int c = cnts[tid];
        int gt = c;
        gt += __shfl_xor_sync(0xffffffffu, gt, 1);
        gt += __shfl_xor_sync(0xffffffffu, gt, 2);
        gt += __shfl_xor_sync(0xffffffffu, gt, 4);
        const int cp = c + (((lane & 7) == 7) ? (((gt + 15) & ~15) - gt) : 0);
        int inc = cp;
#pragma unroll
        for (int o = 1; o < 32; o <<= 1) {
            int t = __shfl_up_sync(0xffffffffu, inc, o);
            if (lane >= o) inc += t;
        }
        if (lane == 31) warp_sums[wid] = inc;
        __syncthreads();
        int woff = 0;
#pragma unroll
        for (int w = 0; w < G_NT / 32; w++) woff += (w < wid) ? warp_sums[w] : 0;
        start[tid] = woff + inc - cp;
        if (tid == G_NT - 1) start[NB] = woff + inc;
    }
    __syncthreads();
#pragma unroll
    for (int j = 0; j < G_PER; j++) {
        const uint32_t le = r[j].x >> 24;
        const uint32_t pos = min((uint32_t)start[le] + (r[j].y >> 16), (uint32_t)CAPS);
        sidx[pos] = (r[j].x & 0xffffffu) | (0x1000000u << (le & 7));
        sc2[pos] = (unsigned short)(r[j].y);
    }
    __syncthreads();
    {
        const int nch = start[NB] >> 2;
        for (int i = tid; i < nch; i += G_NT) {
            const uint2 a = reinterpret_cast<const uint2*>(sc2)[i];
            const uint4 w = reinterpret_cast<const uint4*>(sidx)[i];
            soh[i] = prmt(prmt(w.x, w.y, 0x0073), prmt(w.z, w.w, 0x0073), 0x5410);
            uint32_t x0 = mul_bf16x2(a.x, f0), x1 = mul_bf16x2(a.y, f0);
            uint32_t x2 = mul_bf16x2(a.x, f1), x3 = mul_bf16x2(a.y, f1);
            uint32_t x4 = mul_bf16x2(a.x, f2), x5 = mul_bf16x2(a.y, f2);
            uint32_t t = mul_bf16x2(__vmaxu2(a.x & 0x7fff7fffu, a.y & 0x7fff7fffu), fmaxp);
            uint4 o; uint2 o2;
            if ((t >> 16) < 0x4300u && (t & 0xffffu) < 0x4300u) {
                o.x = cos_fast_bf16x2(x0); o.y = cos_fast_bf16x2(x1);
                o.z = cos_fast_bf16x2(x2); o.w = cos_fast_bf16x2(x3);
                o2.x = cos_fast_bf16x2(x4); o2.y = cos_fast_bf16x2(x5);
            } else {
                o.x = cos_slow_bf16x2(x0); o.y = cos_slow_bf16x2(x1);
                o.z = cos_slow_bf16x2(x2); o.w = cos_slow_bf16x2(x3);
                o2.x = cos_slow_bf16x2(x4); o2.y = cos_slow_bf16x2(x5);
            }
            sc01[i] = o;
            reinterpret_cast<uint2*>(sc2)[i] = o2;
        }
    }
    __syncthreads();

    const int g = lane >> 2, q = lane & 3;
    constexpr int GPW = NGRP / (G_NT / 32);
    const int grp0 = wid * GPW;
    const int wend = start[(grp0 + GPW) * 8];
    const unsigned char* mb = reinterpret_cast<const unsigned char*>(p.m);

    const uint32_t ring = smem_u32(smem_raw + SM_RING) + wid * (G_STAGES * 512);
    const int cj = lane >> 1;
    const uint32_t cdst = (uint32_t)((lane & 1) * 256 + (((cj >> 2) * 2 + (cj & 1) + ((cj >> 1) & 1) * 8) * 16));
    const unsigned char* msrc = mb + (lane & 1) * 16;
    const uint32_t lsrc = (uint32_t)(((lane >> 3) & 1) * 256 + ((lane >> 4) * 8 + (lane & 7)) * 16);

    int ipos = start[grp0 * 8];
    int islot = 0;
#pragma unroll
    for (int k = 0; k < G_STAGES - 1; k++) {
        if (ipos < wend) cp_async_row(ring + islot * 512 + cdst, msrc, sidx[ipos + cj]);
        cp_async_commit();
        ipos += 16; islot++;
    }

    uint32_t adown[4], aup[4], asbf[NL][2], arb[2];
    {
        const unsigned short* wd = reinterpret_cast<const unsigned short*>(p.w_down);
        const unsigned short* wu = reinterpret_cast<const unsigned short*>(p.w_up);
        const unsigned short* ws = reinterpret_cast<const unsigned short*>(p.w_sbf);
        const unsigned short* wr = reinterpret_cast<const unsigned short*>(p.w_rbf);
        adown[0] = (uint32_t)wd[(2 * q) * DE + g] | ((uint32_t)wd[(2 * q + 1) * DE + g] << 16);
        adown[1] = (uint32_t)wd[(2 * q) * DE + g + 8] | ((uint32_t)wd[(2 * q + 1) * DE + g + 8] << 16);
        adown[2] = (uint32_t)wd[(2 * q + 8) * DE + g] | ((uint32_t)wd[(2 * q + 9) * DE + g] << 16);
        adown[3] = (uint32_t)wd[(2 * q + 8) * DE + g + 8] | ((uint32_t)wd[(2 * q + 9) * DE + g + 8] << 16);
#pragma unroll
        for (int l = 0; l < NL; l++) {
            asbf[l][0] = (uint32_t)ws[((2 * q) * NL + l) * DE + g] | ((uint32_t)ws[((2 * q + 1) * NL + l) * DE + g] << 16);
            asbf[l][1] = (uint32_t)ws[((2 * q) * NL + l) * DE + g + 8] | ((uint32_t)ws[((2 * q + 1) * NL + l) * DE + g + 8] << 16);
        }
        const int cA = 2 * g, cB = 2 * g + 1;
        aup[0] = (uint32_t)wu[(2 * q) * DE + cA] | ((uint32_t)wu[(2 * q + 1) * DE + cA] << 16);
        aup[1] = (uint32_t)wu[(2 * q) * DE + cB] | ((uint32_t)wu[(2 * q + 1) * DE + cB] << 16);
        aup[2] = (uint32_t)wu[(2 * q + 8) * DE + cA] | ((uint32_t)wu[(2 * q + 9) * DE + cA] << 16);
        aup[3] = (uint32_t)wu[(2 * q + 8) * DE + cB] | ((uint32_t)wu[(2 * q + 9) * DE + cB] << 16);
        arb[0] = (uint32_t)wr[(2 * q) * DE + cA] | ((uint32_t)wr[(2 * q + 1) * DE + cA] << 16);
        arb[1] = (uint32_t)wr[(2 * q) * DE + cB] | ((uint32_t)wr[(2 * q + 1) * DE + cB] << 16);
    }
    const uint32_t cen = reinterpret_cast<const uint32_t*>(p.centers)[q];
    const unsigned short* dist16 = reinterpret_cast<const unsigned short*>(p.dist);

    int pos = start[grp0 * 8];
    int cslot = 0;
#pragma unroll 1
    for (int gi = 0; gi < GPW; gi++) {
        const int grp = grp0 + gi;
        const int e = start[(grp + 1) * 8];
        const int e0 = bin * NB + grp * 8;
        const int eg = e0 + g;
        const int ea = e0 + 2 * q;
        uint32_t dg = (eg < p.E) ? (uint32_t)dist16[eg] : 0u;
        const uint32_t moff = (uint32_t)ea * 32u + 4u * g;
        uint32_t ma = (ea < p.E) ? __ldg(reinterpret_cast<const uint32_t*>(mb + moff)) : 0u;
        uint32_t mbv = (ea + 1 < p.E) ? __ldg(reinterpret_cast<const uint32_t*>(mb + moff + 32)) : 0u;

        float D[NL][4];
#pragma unroll
        for (int l = 0; l < NL; l++)
#pragma unroll
            for (int c = 0; c < 4; c++) D[l][c] = 0.f;
#pragma unroll 1
        for (; pos < e; pos += 16) {
            if (ipos < wend) cp_async_row(ring + islot * 512 + cdst, msrc, sidx[ipos + cj]);
            cp_async_commit();
            ipos += 16; islot = (islot == G_STAGES - 1) ? 0 : islot + 1;
            const int ch = (pos >> 2) + q;
            const uint4 c01 = sc01[ch];
            const uint2 c2 = reinterpret_cast<const uint2*>(sc2)[ch];
            const uint32_t kb = ((soh[ch] >> g) & 0x01010101u) * 0xffu;
            const uint32_t k01 = prmt(kb, 0, 0x1100), k23 = prmt(kb, 0, 0x3322);
            cp_async_wait<G_STAGES - 1>();
            __syncwarp();
            uint32_t a[4];
            ldsm_x4_trans(a, ring + cslot * 512 + lsrc);
            cslot = (cslot == G_STAGES - 1) ? 0 : cslot + 1;
            mma16816(D[0], a, c01.x & k01, c01.y & k23);
            mma16816(D[1], a, c01.z & k01, c01.w & k23);
            mma16816(D[2], a, c2.x & k01, c2.y & k23);
        }
        const uint32_t brbf = rbf_bf16x2(dg * 0x10001u, cen);
        float agg[4] = {0.f, 0.f, 0.f, 0.f};
#pragma unroll
        for (int l = 0; l < NL; l++) {
            uint32_t h0 = pack_bf16(D[l][0], D[l][1]);
            uint32_t h1 = pack_bf16(D[l][2], D[l][3]);
            uint32_t l0 = pack_bf16(D[l][0] - bf16lo(h0), D[l][1] - bf16hi(h0));
            uint32_t l1 = pack_bf16(D[l][2] - bf16lo(h1), D[l][3] - bf16hi(h1));
            h0 = movm(h0); h1 = movm(h1); l0 = movm(l0); l1 = movm(l1);
            float S[4] = {0.f, 0.f, 0.f, 0.f};
            float G[4] = {0.f, 0.f, 0.f, 0.f};
            mma16816(S, adown, l0, l1);
            mma16816(S, adown, h0, h1);
            mma1688(G, asbf[l], brbf);
#pragma unroll
            for (int c = 0; c < 4; c++) agg[c] = fmaf(S[c], G[c], agg[c]);
        }
        if (ovf) {
            if (ea < p.E) {
                float* pa = g_ovf + (size_t)ea * DE + g;
                agg[0] += __ldcg(pa); agg[2] += __ldcg(pa + 8);
                pa[0] = 0.f; pa[8] = 0.f;
            }
            if (ea + 1 < p.E) {
                float* pb = g_ovf + (size_t)(ea + 1) * DE + g;
                agg[1] += __ldcg(pb); agg[3] += __ldcg(pb + 8);
                pb[0] = 0.f; pb[8] = 0.f;
            }
        }
        {
            uint32_t h0 = pack_bf16(agg[0], agg[1]);
            uint32_t h1 = pack_bf16(agg[2], agg[3]);
            uint32_t l0 = pack_bf16(agg[0] - bf16lo(h0), agg[1] - bf16hi(h0));
            uint32_t l1 = pack_bf16(agg[2] - bf16lo(h1), agg[3] - bf16hi(h1));
            h0 = movm(h0); h1 = movm(h1); l0 = movm(l0); l1 = movm(l1);
            float U[4] = {0.f, 0.f, 0.f, 0.f};
            float R[4] = {0.f, 0.f, 0.f, 0.f};
            mma16816(U, aup, l0, l1);
            mma16816(U, aup, h0, h1);
            mma1688(R, arb, brbf);
            uint32_t oa = pack_bf16(fmaf(U[0], R[0], bf16lo(ma)), fmaf(U[2], R[2], bf16hi(ma)));
            uint32_t ob = pack_bf16(fmaf(U[1], R[1], bf16lo(mbv)), fmaf(U[3], R[3], bf16hi(mbv)));
            unsigned char* ob8 = reinterpret_cast<unsigned char*>(p.out);
            if (ea < p.E) *reinterpret_cast<uint32_t*>(ob8 + moff) = oa;
            if (ea + 1 < p.E) *reinterpret_cast<uint32_t*>(ob8 + moff + 32) = ob;
        }
    }
}

}

extern "C" void kernel_launch(void* const* d_in, const int* in_sizes, int n_in,
                              void* d_out, int out_size) {
    Params p;
    p.m = (const __nv_bfloat16*)d_in[0];
    p.idx_in = (const int*)d_in[1];
    p.idx_out = (const int*)d_in[2];
    p.dist = (const __nv_bfloat16*)d_in[3];
    p.angle = (const __nv_bfloat16*)d_in[4];
    p.centers = (const __nv_bfloat16*)d_in[5];
    p.ang_freq = (const __nv_bfloat16*)d_in[6];
    p.w_rbf = (const __nv_bfloat16*)d_in[7];
    p.w_sbf = (const __nv_bfloat16*)d_in[8];
    p.w_down = (const __nv_bfloat16*)d_in[9];
    p.w_up = (const __nv_bfloat16*)d_in[10];
    p.out = (__nv_bfloat16*)d_out;
    p.E = in_sizes[3];
    p.T = in_sizes[1];
    p.nbins = (p.E + NB - 1) / NB;

    const int smem1 = P_STAGE * 8 + (BINS_PAD + 4) * 4;
    const int smem2 = SM_TOTAL;
    static int nsm = 0;
    if (!nsm) {
        cudaFuncSetAttribute(k_partition, cudaFuncAttributeMaxDynamicSharedMemorySize, smem1);
        cudaFuncSetAttribute(k_gather, cudaFuncAttributeMaxDynamicSharedMemorySize, smem2);
        int dev = 0;
        cudaGetDevice(&dev);
        cudaDeviceGetAttribute(&nsm, cudaDevAttrMultiProcessorCount, dev);
    }
    long long per_sm = ((long long)p.T + nsm - 1) / nsm;
    int k = (int)((per_sm + P_TILE_MAX - 1) / P_TILE_MAX);
    if (k < 1) k = 1;
    long long tile = ((long long)p.T + (long long)k * nsm - 1) / ((long long)k * nsm);
    tile = (tile + 15) & ~15LL;
    if (tile > P_TILE_MAX) tile = P_TILE_MAX;
    if (tile < 16) tile = 16;
    p.tile = (int)tile;
    p.ntiles = (int)(((long long)p.T + tile - 1) / tile);
    int g1 = p.ntiles < nsm ? p.ntiles : nsm;
    if (g1 > 0) k_partition<<<g1, P_NT, smem1>>>(p);
    k_gather<<<p.nbins, G_NT, smem2>>>(p);
}
```

```cpp
#include <cuda_runtime.h>
#include <cuda_bf16.h>
#include <stdint.h>

namespace {

constexpr int DE = 16;
constexpr int NR = 8;
constexpr int NL = 3;

constexpr int NB_LOG = 8;
constexpr int NB = 1 << NB_LOG;
constexpr int MAX_E = 400000;
constexpr int MAX_BINS = (MAX_E + NB - 1) / NB;
constexpr int BINS_PAD = 2048;
constexpr int CAPG = 5120;

constexpr int P_NT = 1024;
constexpr int P_PER = 16;
constexpr int P_TILE_MAX = P_NT * P_PER;
constexpr int P_STAGE = P_TILE_MAX + 3 * MAX_BINS + 16;

constexpr int G_NT = 256;
constexpr int G_PER = CAPG / G_NT;
constexpr int NGRP = NB / 8;
constexpr int CAPS = CAPG + NGRP * 16;
constexpr int G_STAGES = 3;

__device__ uint2 g_records[(size_t)MAX_BINS * CAPG];
__device__ int g_cursor[BINS_PAD];
__device__ float g_ovf[(size_t)MAX_BINS * NB * DE];

__device__ __forceinline__ float bf16r(float x) { return __bfloat162float(__float2bfloat16_rn(x)); }
__device__ __forceinline__ float bf16lo(uint32_t v) { return __uint_as_float(v << 16); }
__device__ __forceinline__ float bf16hi(uint32_t v) { return __uint_as_float(v & 0xffff0000u); }
__device__ __forceinline__ float ldbf(const __nv_bfloat16* p) { return __bfloat162float(*p); }
__device__ __forceinline__ uint32_t smem_u32(const void* p) { return (uint32_t)__cvta_generic_to_shared(p); }

__device__ __forceinline__ uint32_t pack_bf16(float lo, float hi) {
    __nv_bfloat162 v = __floats2bfloat162_rn(lo, hi);
    return *reinterpret_cast<uint32_t*>(&v);
}
__device__ __forceinline__ uint32_t mul_bf16x2(uint32_t a, uint32_t b) {
    __nv_bfloat162 r = __hmul2(*reinterpret_cast<__nv_bfloat162*>(&a), *reinterpret_cast<__nv_bfloat162*>(&b));
    return *reinterpret_cast<uint32_t*>(&r);
}
__device__ __forceinline__ uint32_t sub_bf16x2(uint32_t a, uint32_t b) {
    __nv_bfloat162 r = __hsub2(*reinterpret_cast<__nv_bfloat162*>(&a), *reinterpret_cast<__nv_bfloat162*>(&b));
    return *reinterpret_cast<uint32_t*>(&r);
}
__device__ __forceinline__ uint32_t cos_fast_bf16x2(uint32_t x) {
    return pack_bf16(__cosf(bf16lo(x)), __cosf(bf16hi(x)));
}
__device__ __noinline__ uint32_t cos_slow_bf16x2(uint32_t x) {
    return pack_bf16(cosf(bf16lo(x)), cosf(bf16hi(x)));
}
__device__ __forceinline__ uint32_t rbf_bf16x2(uint32_t dd, uint32_t cc) {
    uint32_t t = sub_bf16x2(dd, cc);
    t = mul_bf16x2(t, t);
    t = mul_bf16x2(t, 0xC120C120u);
    return pack_bf16(__expf(bf16lo(t)), __expf(bf16hi(t)));
}

__device__ __forceinline__ void mma16816(float* d, const uint32_t* a, uint32_t b0, uint32_t b1) {
    asm volatile("mma.sync.aligned.m16n8k16.row.col.f32.bf16.bf16.f32 {%0,%1,%2,%3}, {%4,%5,%6,%7}, {%8,%9}, {%0,%1,%2,%3};"
                 : "+f"(d[0]), "+f"(d[1]), "+f"(d[2]), "+f"(d[3])
                 : "r"(a[0]), "r"(a[1]), "r"(a[2]), "r"(a[3]), "r"(b0), "r"(b1));
}
__device__ __forceinline__ void mma1688(float* d, const uint32_t* a, uint32_t b) {
    asm volatile("mma.sync.aligned.m16n8k8.row.col.f32.bf16.bf16.f32 {%0,%1,%2,%3}, {%4,%5}, {%6}, {%0,%1,%2,%3};"
                 : "+f"(d[0]), "+f"(d[1]), "+f"(d[2]), "+f"(d[3])
                 : "r"(a[0]), "r"(a[1]), "r"(b));
}
__device__ __forceinline__ uint32_t movm(uint32_t a) {
    uint32_t d;
    asm volatile("movmatrix.sync.aligned.m8n8.trans.b16 %0, %1;" : "=r"(d) : "r"(a));
    return d;
}
__device__ __forceinline__ uint32_t prmt(uint32_t a, uint32_t b, uint32_t sel) {
    uint32_t d;
    asm("prmt.b32 %0, %1, %2, %3;" : "=r"(d) : "r"(a), "r"(b), "r"(sel));
    return d;
}
__device__ __forceinline__ void ldsm_x4_trans(uint32_t* r, uint32_t addr) {
    asm volatile("ldmatrix.sync.aligned.m8n8.x4.trans.shared.b16 {%0,%1,%2,%3}, [%4];"
                 : "=r"(r[0]), "=r"(r[1]), "=r"(r[2]), "=r"(r[3]) : "r"(addr) : "memory");
}
__device__ __forceinline__ void cp_async_row(uint32_t dst, const unsigned char* base, uint32_t w) {
    const uint32_t sz = (w >> 24) ? 16u : 0u;
    asm volatile("cp.async.cg.shared.global [%0], [%1], 16, %2;" :: "r"(dst), "l"(base + (w & 0xffffffu)), "r"(sz) : "memory");
}
__device__ __forceinline__ void cp_async_commit() { asm volatile("cp.async.commit_group;" ::: "memory"); }
template <int N> __device__ __forceinline__ void cp_async_wait() { asm volatile("cp.async.wait_group %0;" :: "n"(N) : "memory"); }

struct Params {
    const __nv_bfloat16* m;
    const int* idx_in;
    const int* idx_out;
    const __nv_bfloat16* dist;
    const __nv_bfloat16* angle;
    const __nv_bfloat16* centers;
    const __nv_bfloat16* ang_freq;
    const __nv_bfloat16* w_rbf;
    const __nv_bfloat16* w_sbf;
    const __nv_bfloat16* w_down;
    const __nv_bfloat16* w_up;
    __nv_bfloat16* out;
    int E, T, nbins, ntiles, tile;
};

__device__ __noinline__ void slow_bin(const Params* pp, int bin) {
    const Params& p = *pp;
    for (int t = threadIdx.x; t < p.T; t += blockDim.x) {
        const int out = p.idx_out[t];
        if ((out >> NB_LOG) != bin) continue;
        const int in = p.idx_in[t];
        const float ang = ldbf(p.angle + t);
        float mrow[DE], rb[NR], cb[NL];
        for (int k = 0; k < DE; k++) mrow[k] = ldbf(p.m + (size_t)in * DE + k);
        float d = ldbf(p.dist + out);
        for (int r = 0; r < NR; r++) {
            float u = bf16r(d - ldbf(p.centers + r));
            u = bf16r(u * u);
            u = bf16r(-10.0f * u);
            rb[r] = bf16r(__expf(u));
        }
        for (int l = 0; l < NL; l++) cb[l] = bf16r(cosf(bf16r(ldbf(p.ang_freq + l) * ang)));
        for (int c = 0; c < DE; c++) {
            float md = 0.f, s = 0.f;
            for (int k = 0; k < DE; k++) md = fmaf(mrow[k], ldbf(p.w_down + k * DE + c), md);
            for (int r = 0; r < NR; r++)
                for (int l = 0; l < NL; l++) s = fmaf(rb[r] * cb[l], ldbf(p.w_sbf + (r * NL + l) * DE + c), s);
            atomicAdd(&g_ovf[(size_t)out * DE + c], md * s);
        }
    }
    __threadfence();
}

__device__ __forceinline__ int4 ld4_guard(const int* p, int i, int n, int fill) {
    if (i + 3 < n) return __ldcs(reinterpret_cast<const int4*>(p + i));
    int4 r;
    r.x = (i + 0 < n) ? p[i + 0] : fill;
    r.y = (i + 1 < n) ? p[i + 1] : fill;
    r.z = (i + 2 < n) ? p[i + 2] : fill;
    r.w = fill;
    return r;
}
__device__ __forceinline__ uint2 ld4h_guard(const unsigned short* p, int i, int n) {
    if (i + 3 < n) return __ldcs(reinterpret_cast<const uint2*>(p + i));
    uint32_t a = (i + 0 < n) ? p[i + 0] : 0u, b = (i + 1 < n) ? p[i + 1] : 0u, c = (i + 2 < n) ? p[i + 2] : 0u;
    return make_uint2(a | (b << 16), c);
}

__global__ void __launch_bounds__(P_NT, 1) k_partition(const __grid_constant__ Params p) {
    extern __shared__ __align__(16) unsigned char smem_raw[];
    uint2* stage = reinterpret_cast<uint2*>(smem_raw);
    int* hist = reinterpret_cast<int*>(smem_raw + (size_t)P_STAGE * 8);
    __shared__ int warp_sums[P_NT / 32];
    static_assert(BINS_PAD == 2 * P_NT, "two bins per thread in the scan");

    const int tid = threadIdx.x;
    const int lane = tid & 31, wid = tid >> 5;
    const unsigned short* ang16 = reinterpret_cast<const unsigned short*>(p.angle);

    int4 O[P_PER / 4];
    int tile = blockIdx.x;
    if (tile < p.ntiles) {
        const int base = tile * p.tile, n = min(p.tile, p.T - base);
#pragma unroll
        for (int v = 0; v < P_PER / 4; v++) O[v] = ld4_guard(p.idx_out + base, (v * P_NT + tid) * 4, n, -1);
    }
    reinterpret_cast<int2*>(hist)[tid] = make_int2(0, 0);
    if (tid == 0) hist[BINS_PAD] = 0;
    for (; tile < p.ntiles; tile += gridDim.x) {
        const int base = tile * p.tile, n = min(p.tile, p.T - base);
        __syncthreads();
#pragma unroll
        for (int v = 0; v < P_PER / 4; v++) {
            atomicAdd(&hist[min((uint32_t)O[v].x >> NB_LOG, (uint32_t)BINS_PAD)], 1);
            atomicAdd(&hist[min((uint32_t)O[v].y >> NB_LOG, (uint32_t)BINS_PAD)], 1);
            atomicAdd(&hist[min((uint32_t)O[v].z >> NB_LOG, (uint32_t)BINS_PAD)], 1);
            atomicAdd(&hist[min((uint32_t)O[v].w >> NB_LOG, (uint32_t)BINS_PAD)], 1);
        }
        int4 I[P_PER / 4];
        uint2 A[P_PER / 4];
#pragma unroll
        for (int v = 0; v < P_PER / 4; v++) {
            I[v] = ld4_guard(p.idx_in + base, (v * P_NT + tid) * 4, n, 0);
            A[v] = ld4h_guard(ang16 + base, (v * P_NT + tid) * 4, n);
        }
        __syncthreads();
        const int2 c2 = reinterpret_cast<int2*>(hist)[tid];
        const int pc0 = (c2.x + 3) & ~3, pc1 = (c2.y + 3) & ~3;
        int g0 = 0, g1 = 0;
        if (pc0) g0 = atomicAdd(&g_cursor[2 * tid], pc0);
        if (pc1) g1 = atomicAdd(&g_cursor[2 * tid + 1], pc1);
        const int s = pc0 + pc1;
        int inc = s;
#pragma unroll
        for (int o = 1; o < 32; o <<= 1) {
            int t = __shfl_up_sync(0xffffffffu, inc, o);
            if (lane >= o) inc += t;
        }
        if (lane == 31) warp_sums[wid] = inc;
        asm volatile("cp.async.bulk.wait_group.read 0;" ::: "memory");
        __syncthreads();
        int woff;
        {
            int ws = warp_sums[lane];
            int winc = ws;
#pragma unroll
            for (int o = 1; o < 32; o <<= 1) {
                int t = __shfl_up_sync(0xffffffffu, winc, o);
                if (lane >= o) winc += t;
            }
            woff = __shfl_sync(0xffffffffu, winc - ws, wid);
        }
        const int e0 = woff + inc - s, e1 = e0 + pc0;
        reinterpret_cast<int2*>(hist)[tid] = make_int2(e0, e1);
        if (tid == 0) hist[BINS_PAD] = P_STAGE;
        for (int k = c2.x; k < pc0; k++) stage[e0 + k] = make_uint2(0u, 0xffffffffu);
        for (int k = c2.y; k < pc1; k++) stage[e1 + k] = make_uint2(0u, 0xffffffffu);
        __syncthreads();
#pragma unroll
        for (int v = 0; v < P_PER / 4; v++) {
            const uint32_t o[4] = {(uint32_t)O[v].x, (uint32_t)O[v].y, (uint32_t)O[v].z, (uint32_t)O[v].w};
            const uint32_t in[4] = {(uint32_t)I[v].x, (uint32_t)I[v].y, (uint32_t)I[v].z, (uint32_t)I[v].w};
            const uint32_t an[4] = {A[v].x & 0xffffu, A[v].x >> 16, A[v].y & 0xffffu, A[v].y >> 16};
#pragma unroll
            for (int u = 0; u < 4; u++) {
                int pos = atomicAdd(&hist[min(o[u] >> NB_LOG, (uint32_t)BINS_PAD)], 1);
                stage[min(pos, P_STAGE - 1)] = make_uint2((in[u] << 5) | (0x1000000u << (o[u] & 7)), an[u] | ((o[u] & 255u) << 16));
            }
        }
        {
            const int nt = tile + gridDim.x;
            if (nt < p.ntiles) {
                const int nbase = nt * p.tile, nn = min(p.tile, p.T - nbase);
#pragma unroll
                for (int v = 0; v < P_PER / 4; v++) O[v] = ld4_guard(p.idx_out + nbase, (v * P_NT + tid) * 4, nn, -1);
            }
        }
        asm volatile("fence.proxy.async.shared::cta;" ::: "memory");
        __syncthreads();
        if (pc0 && g0 + pc0 <= CAPG)
            asm volatile("cp.async.bulk.global.shared::cta.bulk_group [%0], [%1], %2;"
                         :: "l"(g_records + (size_t)(2 * tid) * CAPG + g0), "r"(smem_u32(stage + e0)), "r"(pc0 * 8) : "memory");
        if (pc1 && g1 + pc1 <= CAPG)
            asm volatile("cp.async.bulk.global.shared::cta.bulk_group [%0], [%1], %2;"
                         :: "l"(g_records + (size_t)(2 * tid + 1) * CAPG + g1), "r"(smem_u32(stage + e1)), "r"(pc1 * 8) : "memory");
        asm volatile("cp.async.bulk.commit_group;" ::: "memory");
        reinterpret_cast<int2*>(hist)[tid] = make_int2(0, 0);
        if (tid == 0) hist[BINS_PAD] = 0;
    }
    asm volatile("cp.async.bulk.wait_group 0;" ::: "memory");
}

constexpr int SM_IDX = 0;
constexpr int SM_C01 = SM_IDX + (CAPS + 16) * 4;
constexpr int SM_C2 = SM_C01 + CAPS * 4;
constexpr int SM_OH = SM_C2 + (CAPS + 16) * 2;
constexpr int SM_RING = SM_OH + CAPS;
constexpr int SM_TOTAL = SM_RING + (G_NT / 32) * G_STAGES * 512;

__global__ void __launch_bounds__(G_NT, 3) k_gather(const __grid_constant__ Params p) {
    extern __shared__ __align__(128) unsigned char smem_raw[];
    uint32_t* sidx = reinterpret_cast<uint32_t*>(smem_raw + SM_IDX);
    uint4* sc01 = reinterpret_cast<uint4*>(smem_raw + SM_C01);
    unsigned short* sc2 = reinterpret_cast<unsigned short*>(smem_raw + SM_C2);
    uint32_t* soh = reinterpret_cast<uint32_t*>(smem_raw + SM_OH);
    __shared__ int cnts[NB];
    __shared__ int start[NB + 1];
    __shared__ int warp_sums[G_NT / 32];
    static_assert(NB == G_NT, "one edge per thread in the scan");

    const int tid = threadIdx.x;
    const int lane = tid & 31, wid = tid >> 5;
    const int bin = blockIdx.x;
    const int total = g_cursor[bin];
    const bool ovf = total > CAPG;
    const int n = ovf ? 0 : total;
    if (ovf) slow_bin(&p, bin);

    const uint4* rec = reinterpret_cast<const uint4*>(g_records + (size_t)bin * CAPG) + tid;
    uint4 r[G_PER / 2];
#pragma unroll
    for (int j = 0; j < G_PER / 2; j++) {
        r[j] = make_uint4(0u, 0xffffffffu, 0u, 0xffffffffu);
        if ((j * G_NT + tid) * 2 < n) r[j] = __ldcs(rec + j * G_NT);
    }
    cnts[tid] = 0;
    const unsigned short* fq = reinterpret_cast<const unsigned short*>(p.ang_freq);
    const uint32_t f0 = (uint32_t)fq[0] * 0x10001u, f1 = (uint32_t)fq[1] * 0x10001u, f2 = (uint32_t)fq[2] * 0x10001u;
    const uint32_t fmaxp = max(max(f0 & 0x7fff7fffu, f1 & 0x7fff7fffu), f2 & 0x7fff7fffu);
    __syncthreads();
    if (tid == 0) g_cursor[bin] = 0;
#pragma unroll
    for (int j = 0; j < G_PER / 2; j++) {
        if ((int)r[j].y >= 0) atomicAdd(&cnts[r[j].y >> 16], 1);
        if ((int)r[j].w >= 0) atomicAdd(&cnts[r[j].w >> 16], 1);
    }
    __syncthreads();
    {
        const int c = cnts[tid];
        int gt = c;
        gt += __shfl_xor_sync(0xffffffffu, gt, 1);
        gt += __shfl_xor_sync(0xffffffffu, gt, 2);
        gt += __shfl_xor_sync(0xffffffffu, gt, 4);
        const int npad = ((gt + 15) & ~15) - gt;
        const int cp = c + (((lane & 7) == 7) ? npad : 0);
        int inc = cp;
#pragma unroll
        for (int o = 1; o < 32; o <<= 1) {
            int t = __shfl_up_sync(0xffffffffu, inc, o);
            if (lane >= o) inc += t;
        }
        if (lane == 31) warp_sums[wid] = inc;
        __syncthreads();
        int woff = 0;
#pragma unroll
        for (int w = 0; w < G_NT / 32; w++) woff += (w < wid) ? warp_sums[w] : 0;
        const int st = woff + inc - cp;
        start[tid] = st;
        cnts[tid] = st;
        if (tid == G_NT - 1) start[NB] = woff + inc;
        const int gend = __shfl_sync(0xffffffffu, woff + inc, lane | 7);
        const int k = lane & 7;
        if (k < npad) { sidx[gend - 1 - k] = 0u; sc2[gend - 1 - k] = 0; }
        if (k + 8 < npad) { sidx[gend - 9 - k] = 0u; sc2[gend - 9 - k] = 0; }
    }
    __syncthreads();
#pragma unroll
    for (int j = 0; j < G_PER / 2; j++) {
        if ((int)r[j].y >= 0) {
            const int pos = atomicAdd(&cnts[r[j].y >> 16], 1);
            sidx[pos] = r[j].x;
            sc2[pos] = (unsigned short)r[j].y;
        }
        if ((int)r[j].w >= 0) {
            const int pos = atomicAdd(&cnts[r[j].w >> 16], 1);
            sidx[pos] = r[j].z;
            sc2[pos] = (unsigned short)r[j].w;
        }
    }
    __syncthreads();
    {
        const int nch = start[NB] >> 2;
        for (int i = tid; i < nch; i += G_NT) {
            const uint2 a = reinterpret_cast<const uint2*>(sc2)[i];
            const uint4 w = reinterpret_cast<const uint4*>(sidx)[i];
            soh[i] = prmt(prmt(w.x, w.y, 0x0073), prmt(w.z, w.w, 0x0073), 0x5410);
            uint32_t x0 = mul_bf16x2(a.x, f0), x1 = mul_bf16x2(a.y, f0);
            uint32_t x2 = mul_bf16x2(a.x, f1), x3 = mul_bf16x2(a.y, f1);
            uint32_t x4 = mul_bf16x2(a.x, f2), x5 = mul_bf16x2(a.y, f2);
            uint32_t t = mul_bf16x2(__vmaxu2(a.x & 0x7fff7fffu, a.y & 0x7fff7fffu), fmaxp);
            uint4 o; uint2 o2;
            if ((t >> 16) < 0x4300u && (t & 0xffffu) < 0x4300u) {
                o.x = cos_fast_bf16x2(x0); o.y = cos_fast_bf16x2(x1);
                o.z = cos_fast_bf16x2(x2); o.w = cos_fast_bf16x2(x3);
                o2.x = cos_fast_bf16x2(x4); o2.y = cos_fast_bf16x2(x5);
            } else {
                o.x = cos_slow_bf16x2(x0); o.y = cos_slow_bf16x2(x1);
                o.z = cos_slow_bf16x2(x2); o.w = cos_slow_bf16x2(x3);
                o2.x = cos_slow_bf16x2(x4); o2.y = cos_slow_bf16x2(x5);
            }
            sc01[i] = o;
            reinterpret_cast<uint2*>(sc2)[i] = o2;
        }
    }
    __syncthreads();

    const int g = lane >> 2, q = lane & 3;
    constexpr int GPW = NGRP / (G_NT / 32);
    const int grp0 = wid * GPW;
    const int wend = start[(grp0 + GPW) * 8];
    const unsigned char* mb = reinterpret_cast<const unsigned char*>(p.m);

    const uint32_t ring = smem_u32(smem_raw + SM_RING) + wid * (G_STAGES * 512);
    const int cj = lane >> 1;
    const uint32_t cdst = (uint32_t)((lane & 1) * 256 + (((cj >> 2) * 2 + (cj & 1) + ((cj >> 1) & 1) * 8) * 16));
    const unsigned char* msrc = mb + (lane & 1) * 16;
    const uint32_t lsrc = (uint32_t)(((lane >> 3) & 1) * 256 + ((lane >> 4) * 8 + (lane & 7)) * 16);

    int ipos = start[grp0 * 8];
    int islot = 0;
#pragma unroll
    for (int k = 0; k < G_STAGES - 1; k++) {
        if (ipos < wend) cp_async_row(ring + islot * 512 + cdst, msrc, sidx[ipos + cj]);
        cp_async_commit();
        ipos += 16; islot++;
    }

    uint32_t adown[4], aup[4], asbf[NL][2], arb[2];
    {
        const unsigned short* wd = reinterpret_cast<const unsigned short*>(p.w_down);
        const unsigned short* wu = reinterpret_cast<const unsigned short*>(p.w_up);
        const unsigned short* ws = reinterpret_cast<const unsigned short*>(p.w_sbf);
        const unsigned short* wr = reinterpret_cast<const unsigned short*>(p.w_rbf);
        adown[0] = (uint32_t)wd[(2 * q) * DE + g] | ((uint32_t)wd[(2 * q + 1) * DE + g] << 16);
        adown[1] = (uint32_t)wd[(2 * q) * DE + g + 8] | ((uint32_t)wd[(2 * q + 1) * DE + g + 8] << 16);
        adown[2] = (uint32_t)wd[(2 * q + 8) * DE + g] | ((uint32_t)wd[(2 * q + 9) * DE + g] << 16);
        adown[3] = (uint32_t)wd[(2 * q + 8) * DE + g + 8] | ((uint32_t)wd[(2 * q + 9) * DE + g + 8] << 16);
#pragma unroll
        for (int l = 0; l < NL; l++) {
            asbf[l][0] = (uint32_t)ws[((2 * q) * NL + l) * DE + g] | ((uint32_t)ws[((2 * q + 1) * NL + l) * DE + g] << 16);
            asbf[l][1] = (uint32_t)ws[((2 * q) * NL + l) * DE + g + 8] | ((uint32_t)ws[((2 * q + 1) * NL + l) * DE + g + 8] << 16);
        }
        const int cA = 2 * g, cB = 2 * g + 1;
        aup[0] = (uint32_t)wu[(2 * q) * DE + cA] | ((uint32_t)wu[(2 * q + 1) * DE + cA] << 16);
        aup[1] = (uint32_t)wu[(2 * q) * DE + cB] | ((uint32_t)wu[(2 * q + 1) * DE + cB] << 16);
        aup[2] = (uint32_t)wu[(2 * q + 8) * DE + cA] | ((uint32_t)wu[(2 * q + 9) * DE + cA] << 16);
        aup[3] = (uint32_t)wu[(2 * q + 8) * DE + cB] | ((uint32_t)wu[(2 * q + 9) * DE + cB] << 16);
        arb[0] = (uint32_t)wr[(2 * q) * DE + cA] | ((uint32_t)wr[(2 * q + 1) * DE + cA] << 16);
        arb[1] = (uint32_t)wr[(2 * q) * DE + cB] | ((uint32_t)wr[(2 * q + 1) * DE + cB] << 16);
    }
    const uint32_t cen = reinterpret_cast<const uint32_t*>(p.centers)[q];
    const unsigned short* dist16 = reinterpret_cast<const unsigned short*>(p.dist);

    int pos = start[grp0 * 8];
    int cslot = 0;
#pragma unroll 1
    for (int gi = 0; gi < GPW; gi++) {
        const int grp = grp0 + gi;
        const int e = start[(grp + 1) * 8];
        const int e0 = bin * NB + grp * 8;
        const int eg = e0 + g;
        const int ea = e0 + 2 * q;
        uint32_t dg = (eg < p.E) ? (uint32_t)dist16[eg] : 0u;
        const uint32_t moff = (uint32_t)ea * 32u + 4u * g;
        uint32_t ma = (ea < p.E) ? __ldg(reinterpret_cast<const uint32_t*>(mb + moff)) : 0u;
        uint32_t mbv = (ea + 1 < p.E) ? __ldg(reinterpret_cast<const uint32_t*>(mb + moff + 32)) : 0u;

        float D[NL][4];
#pragma unroll
        for (int l = 0; l < NL; l++)
#pragma unroll
            for (int c = 0; c < 4; c++) D[l][c] = 0.f;
#pragma unroll 1
        for (; pos < e; pos += 16) {
            if (ipos < wend) cp_async_row(ring + islot * 512 + cdst, msrc, sidx[ipos + cj]);
            cp_async_commit();
            ipos += 16; islot = (islot == G_STAGES - 1) ? 0 : islot + 1;
            const int ch = (pos >> 2) + q;
            const uint4 c01 = sc01[ch];
            const uint2 c2 = reinterpret_cast<const uint2*>(sc2)[ch];
            const uint32_t kb = ((soh[ch] >> g) & 0x01010101u) * 0xffu;
            const uint32_t k01 = prmt(kb, 0, 0x1100), k23 = prmt(kb, 0, 0x3322);
            cp_async_wait<G_STAGES - 1>();
            __syncwarp();
            uint32_t a[4];
            ldsm_x4_trans(a, ring + cslot * 512 + lsrc);
            cslot = (cslot == G_STAGES - 1) ? 0 : cslot + 1;
            mma16816(D[0], a, c01.x & k01, c01.y & k23);
            mma16816(D[1], a, c01.z & k01, c01.w & k23);
            mma16816(D[2], a, c2.x & k01, c2.y & k23);
        }
        const uint32_t brbf = rbf_bf16x2(dg * 0x10001u, cen);
        float agg[4] = {0.f, 0.f, 0.f, 0.f};
#pragma unroll
        for (int l = 0; l < NL; l++) {
            uint32_t h0 = pack_bf16(D[l][0], D[l][1]);
            uint32_t h1 = pack_bf16(D[l][2], D[l][3]);
            uint32_t l0 = pack_bf16(D[l][0] - bf16lo(h0), D[l][1] - bf16hi(h0));
            uint32_t l1 = pack_bf16(D[l][2] - bf16lo(h1), D[l][3] - bf16hi(h1));
            h0 = movm(h0); h1 = movm(h1); l0 = movm(l0); l1 = movm(l1);
            float S[4] = {0.f, 0.f, 0.f, 0.f};
            float G[4] = {0.f, 0.f, 0.f, 0.f};
            mma16816(S, adown, l0, l1);
            mma16816(S, adown, h0, h1);
            mma1688(G, asbf[l], brbf);
#pragma unroll
            for (int c = 0; c < 4; c++) agg[c] = fmaf(S[c], G[c], agg[c]);
        }
        if (ovf) {
            if (ea < p.E) {
                float* pa = g_ovf + (size_t)ea * DE + g;
                agg[0] += __ldcg(pa); agg[2] += __ldcg(pa + 8);
                pa[0] = 0.f; pa[8] = 0.f;
            }
            if (ea + 1 < p.E) {
                float* pb = g_ovf + (size_t)(ea + 1) * DE + g;
                agg[1] += __ldcg(pb); agg[3] += __ldcg(pb + 8);
                pb[0] = 0.f; pb[8] = 0.f;
            }
        }
        {
            uint32_t h0 = pack_bf16(agg[0], agg[1]);
            uint32_t h1 = pack_bf16(agg[2], agg[3]);
            uint32_t l0 = pack_bf16(agg[0] - bf16lo(h0), agg[1] - bf16hi(h0));
            uint32_t l1 = pack_bf16(agg[2] - bf16lo(h1), agg[3] - bf16hi(h1));
            h0 = movm(h0); h1 = movm(h1); l0 = movm(l0); l1 = movm(l1);
            float U[4] = {0.f, 0.f, 0.f, 0.f};
            float R[4] = {0.f, 0.f, 0.f, 0.f};
            mma16816(U, aup, l0, l1);
            mma16816(U, aup, h0, h1);
            mma1688(R, arb, brbf);
            uint32_t oa = pack_bf16(fmaf(U[0], R[0], bf16lo(ma)), fmaf(U[2], R[2], bf16hi(ma)));
            uint32_t ob = pack_bf16(fmaf(U[1], R[1], bf16lo(mbv)), fmaf(U[3], R[3], bf16hi(mbv)));
            unsigned char* ob8 = reinterpret_cast<unsigned char*>(p.out);
            if (ea < p.E) *reinterpret_cast<uint32_t*>(ob8 + moff) = oa;
            if (ea + 1 < p.E) *reinterpret_cast<uint32_t*>(ob8 + moff + 32) = ob;
        }
    }
}

}

extern "C" void kernel_launch(void* const* d_in, const int* in_sizes, int n_in,
                              void* d_out, int out_size) {
    Params p;
    p.m = (const __nv_bfloat16*)d_in[0];
    p.idx_in = (const int*)d_in[1];
    p.idx_out = (const int*)d_in[2];
    p.dist = (const __nv_bfloat16*)d_in[3];
    p.angle = (const __nv_bfloat16*)d_in[4];
    p.centers = (const __nv_bfloat16*)d_in[5];
    p.ang_freq = (const __nv_bfloat16*)d_in[6];
    p.w_rbf = (const __nv_bfloat16*)d_in[7];
    p.w_sbf = (const __nv_bfloat16*)d_in[8];
    p.w_down = (const __nv_bfloat16*)d_in[9];
    p.w_up = (const __nv_bfloat16*)d_in[10];
    p.out = (__nv_bfloat16*)d_out;
    p.E = in_sizes[3];
    p.T = in_sizes[1];
    p.nbins = (p.E + NB - 1) / NB;

    const int smem1 = P_STAGE * 8 + (BINS_PAD + 4) * 4;
    const int smem2 = SM_TOTAL;
    static int nsm = 0;
    if (!nsm) {
        cudaFuncSetAttribute(k_partition, cudaFuncAttributeMaxDynamicSharedMemorySize, smem1);
        cudaFuncSetAttribute(k_gather, cudaFuncAttributeMaxDynamicSharedMemorySize, smem2);
        int dev = 0;
        cudaGetDevice(&dev);
        cudaDeviceGetAttribute(&nsm, cudaDevAttrMultiProcessorCount, dev);
    }
    long long per_sm = ((long long)p.T + nsm - 1) / nsm;
    int k = (int)((per_sm + P_TILE_MAX - 1) / P_TILE_MAX);
    if (k < 1) k = 1;
    long long tile = ((long long)p.T + (long long)k * nsm - 1) / ((long long)k * nsm);
    tile = (tile + 15) & ~15LL;
    if (tile > P_TILE_MAX) tile = P_TILE_MAX;
    if (tile < 16) tile = 16;
    p.tile = (int)tile;
    p.ntiles = (int)(((long long)p.T + tile - 1) / tile);
    int g1 = p.ntiles < nsm ? p.ntiles : nsm;
    if (g1 > 0) k_partition<<<g1, P_NT, smem1>>>(p);
    k_gather<<<p.nbins, G_NT, smem2>>>(p);
}
```

```cpp
#include <cuda_runtime.h>
#include <cuda_bf16.h>
#include <stdint.h>

namespace {

constexpr int DE = 16;
constexpr int NR = 8;
constexpr int NL = 3;

constexpr int NB_LOG = 8;
constexpr int NB = 1 << NB_LOG;
constexpr int MAX_E = 400000;
constexpr int MAX_BINS = (MAX_E + NB - 1) / NB;
constexpr int BINS_PAD = 2048;
constexpr int CAPG = 5120;

constexpr int P_NT = 1024;
constexpr int P_PER = 16;
constexpr int P_TILE_MAX = P_NT * P_PER;
constexpr int P_STAGE = P_TILE_MAX + 3 * MAX_BINS + 16;

#define CFG_G_NT 256
#define CFG_G_BLOCKS 3
#define CFG_G_STAGES 3
constexpr int G_NT = CFG_G_NT;
constexpr int G_BLOCKS = CFG_G_BLOCKS;
constexpr int G_PER = CAPG / G_NT;
constexpr int NGRP = NB / 8;
constexpr int CAPS = CAPG + NGRP * 16;
constexpr int G_STAGES = CFG_G_STAGES;

__device__ uint2 g_records[(size_t)MAX_BINS * CAPG];
__device__ int g_cursor[BINS_PAD];
__device__ float g_ovf[(size_t)MAX_BINS * NB * DE];

__device__ __forceinline__ float bf16r(float x) { return __bfloat162float(__float2bfloat16_rn(x)); }
__device__ __forceinline__ float bf16lo(uint32_t v) { return __uint_as_float(v << 16); }
__device__ __forceinline__ float bf16hi(uint32_t v) { return __uint_as_float(v & 0xffff0000u); }
__device__ __forceinline__ float ldbf(const __nv_bfloat16* p) { return __bfloat162float(*p); }
__device__ __forceinline__ uint32_t smem_u32(const void* p) { return (uint32_t)__cvta_generic_to_shared(p); }

__device__ __forceinline__ uint32_t pack_bf16(float lo, float hi) {
    __nv_bfloat162 v = __floats2bfloat162_rn(lo, hi);
    return *reinterpret_cast<uint32_t*>(&v);
}
__device__ __forceinline__ uint32_t mul_bf16x2(uint32_t a, uint32_t b) {
    __nv_bfloat162 r = __hmul2(*reinterpret_cast<__nv_bfloat162*>(&a), *reinterpret_cast<__nv_bfloat162*>(&b));
    return *reinterpret_cast<uint32_t*>(&r);
}
__device__ __forceinline__ uint32_t sub_bf16x2(uint32_t a, uint32_t b) {
    __nv_bfloat162 r = __hsub2(*reinterpret_cast<__nv_bfloat162*>(&a), *reinterpret_cast<__nv_bfloat162*>(&b));
    return *reinterpret_cast<uint32_t*>(&r);
}
__device__ __forceinline__ uint32_t cos_fast_bf16x2(uint32_t x) {
    return pack_bf16(__cosf(bf16lo(x)), __cosf(bf16hi(x)));
}
__device__ __noinline__ uint32_t cos_slow_bf16x2(uint32_t x) {
    return pack_bf16(cosf(bf16lo(x)), cosf(bf16hi(x)));
}
__device__ __forceinline__ uint32_t rbf_bf16x2(uint32_t dd, uint32_t cc) {
    uint32_t t = sub_bf16x2(dd, cc);
    t = mul_bf16x2(t, t);
    t = mul_bf16x2(t, 0xC120C120u);
    return pack_bf16(__expf(bf16lo(t)), __expf(bf16hi(t)));
}

__device__ __forceinline__ void mma16816(float* d, const uint32_t* a, uint32_t b0, uint32_t b1) {
    asm volatile("mma.sync.aligned.m16n8k16.row.col.f32.bf16.bf16.f32 {%0,%1,%2,%3}, {%4,%5,%6,%7}, {%8,%9}, {%0,%1,%2,%3};"
                 : "+f"(d[0]), "+f"(d[1]), "+f"(d[2]), "+f"(d[3])
                 : "r"(a[0]), "r"(a[1]), "r"(a[2]), "r"(a[3]), "r"(b0), "r"(b1));
}
__device__ __forceinline__ void mma1688(float* d, const uint32_t* a, uint32_t b) {
    asm volatile("mma.sync.aligned.m16n8k8.row.col.f32.bf16.bf16.f32 {%0,%1,%2,%3}, {%4,%5}, {%6}, {%0,%1,%2,%3};"
                 : "+f"(d[0]), "+f"(d[1]), "+f"(d[2]), "+f"(d[3])
                 : "r"(a[0]), "r"(a[1]), "r"(b));
}
__device__ __forceinline__ uint32_t movm(uint32_t a) {
    uint32_t d;
    asm volatile("movmatrix.sync.aligned.m8n8.trans.b16 %0, %1;" : "=r"(d) : "r"(a));
    return d;
}
__device__ __forceinline__ uint32_t prmt(uint32_t a, uint32_t b, uint32_t sel) {
    uint32_t d;
    asm("prmt.b32 %0, %1, %2, %3;" : "=r"(d) : "r"(a), "r"(b), "r"(sel));
    return d;
}
__device__ __forceinline__ void ldsm_x4_trans(uint32_t* r, uint32_t addr) {
    asm volatile("ldmatrix.sync.aligned.m8n8.x4.trans.shared.b16 {%0,%1,%2,%3}, [%4];"
                 : "=r"(r[0]), "=r"(r[1]), "=r"(r[2]), "=r"(r[3]) : "r"(addr) : "memory");
}
__device__ __forceinline__ void cp_async_row(uint32_t dst, const unsigned char* base, uint32_t w) {
    const uint32_t sz = (w >> 24) ? 16u : 0u;
    asm volatile("cp.async.cg.shared.global [%0], [%1], 16, %2;" :: "r"(dst), "l"(base + (w & 0xffffffu)), "r"(sz) : "memory");
}
__device__ __forceinline__ void cp_async_commit() { asm volatile("cp.async.commit_group;" ::: "memory"); }
template <int N> __device__ __forceinline__ void cp_async_wait() { asm volatile("cp.async.wait_group %0;" :: "n"(N) : "memory"); }

struct Params {
    const __nv_bfloat16* m;
    const int* idx_in;
    const int* idx_out;
    const __nv_bfloat16* dist;
    const __nv_bfloat16* angle;
    const __nv_bfloat16* centers;
    const __nv_bfloat16* ang_freq;
    const __nv_bfloat16* w_rbf;
    const __nv_bfloat16* w_sbf;
    const __nv_bfloat16* w_down;
    const __nv_bfloat16* w_up;
    __nv_bfloat16* out;
    int E, T, nbins, ntiles, tile;
};

__device__ __noinline__ void slow_bin(const Params* pp, int bin) {
    const Params& p = *pp;
    for (int t = threadIdx.x; t < p.T; t += blockDim.x) {
        const int out = p.idx_out[t];
        if ((out >> NB_LOG) != bin) continue;
        const int in = p.idx_in[t];
        const float ang = ldbf(p.angle + t);
        float mrow[DE], rb[NR], cb[NL];
        for (int k = 0; k < DE; k++) mrow[k] = ldbf(p.m + (size_t)in * DE + k);
        float d = ldbf(p.dist + out);
        for (int r = 0; r < NR; r++) {
            float u = bf16r(d - ldbf(p.centers + r));
            u = bf16r(u * u);
            u = bf16r(-10.0f * u);
            rb[r] = bf16r(__expf(u));
        }
        for (int l = 0; l < NL; l++) cb[l] = bf16r(cosf(bf16r(ldbf(p.ang_freq + l) * ang)));
        for (int c = 0; c < DE; c++) {
            float md = 0.f, s = 0.f;
            for (int k = 0; k < DE; k++) md = fmaf(mrow[k], ldbf(p.w_down + k * DE + c), md);
            for (int r = 0; r < NR; r++)
                for (int l = 0; l < NL; l++) s = fmaf(rb[r] * cb[l], ldbf(p.w_sbf + (r * NL + l) * DE + c), s);
            atomicAdd(&g_ovf[(size_t)out * DE + c], md * s);
        }
    }
    __threadfence();
}

__device__ __forceinline__ int4 ld4_guard(const int* p, int i, int n, int fill) {
    if (i + 3 < n) return __ldcs(reinterpret_cast<const int4*>(p + i));
    int4 r;
    r.x = (i + 0 < n) ? p[i + 0] : fill;
    r.y = (i + 1 < n) ? p[i + 1] : fill;
    r.z = (i + 2 < n) ? p[i + 2] : fill;
    r.w = fill;
    return r;
}
__device__ __forceinline__ uint2 ld4h_guard(const unsigned short* p, int i, int n) {
    if (i + 3 < n) return __ldcs(reinterpret_cast<const uint2*>(p + i));
    uint32_t a = (i + 0 < n) ? p[i + 0] : 0u, b = (i + 1 < n) ? p[i + 1] : 0u, c = (i + 2 < n) ? p[i + 2] : 0u;
    return make_uint2(a | (b << 16), c);
}

__global__ void __launch_bounds__(P_NT, 1) k_partition(const __grid_constant__ Params p) {
    extern __shared__ __align__(16) unsigned char smem_raw[];
    uint2* stage = reinterpret_cast<uint2*>(smem_raw);
    int* hist = reinterpret_cast<int*>(smem_raw + (size_t)P_STAGE * 8);
    __shared__ int warp_sums[P_NT / 32];
    static_assert(BINS_PAD == 2 * P_NT, "two bins per thread in the scan");

    const int tid = threadIdx.x;
    const int lane = tid & 31, wid = tid >> 5;
    const unsigned short* ang16 = reinterpret_cast<const unsigned short*>(p.angle);

    int4 O[P_PER / 4];
    int tile = blockIdx.x;
    if (tile < p.ntiles) {
        const int base = tile * p.tile, n = min(p.tile, p.T - base);
#pragma unroll
        for (int v = 0; v < P_PER / 4; v++) O[v] = ld4_guard(p.idx_out + base, (v * P_NT + tid) * 4, n, -1);
    }
    reinterpret_cast<int2*>(hist)[tid] = make_int2(0, 0);
    if (tid == 0) hist[BINS_PAD] = 0;
    for (; tile < p.ntiles; tile += gridDim.x) {
        const int base = tile * p.tile, n = min(p.tile, p.T - base);
        __syncthreads();
#pragma unroll
        for (int v = 0; v < P_PER / 4; v++) {
            atomicAdd(&hist[min((uint32_t)O[v].x >> NB_LOG, (uint32_t)BINS_PAD)], 1);
            atomicAdd(&hist[min((uint32_t)O[v].y >> NB_LOG, (uint32_t)BINS_PAD)], 1);
            atomicAdd(&hist[min((uint32_t)O[v].z >> NB_LOG, (uint32_t)BINS_PAD)], 1);
            atomicAdd(&hist[min((uint32_t)O[v].w >> NB_LOG, (uint32_t)BINS_PAD)], 1);
        }
        int4 I[P_PER / 4];
        uint2 A[P_PER / 4];
#pragma unroll
        for (int v = 0; v < P_PER / 4; v++) {
            I[v] = ld4_guard(p.idx_in + base, (v * P_NT + tid) * 4, n, 0);
            A[v] = ld4h_guard(ang16 + base, (v * P_NT + tid) * 4, n);
        }
        __syncthreads();
        const int2 c2 = reinterpret_cast<int2*>(hist)[tid];
        const int pc0 = (c2.x + 3) & ~3, pc1 = (c2.y + 3) & ~3;
        int g0 = 0, g1 = 0;
        if (pc0) g0 = atomicAdd(&g_cursor[2 * tid], pc0);
        if (pc1) g1 = atomicAdd(&g_cursor[2 * tid + 1], pc1);
        const int s = pc0 + pc1;
        int inc = s;
#pragma unroll
        for (int o = 1; o < 32; o <<= 1) {
            int t = __shfl_up_sync(0xffffffffu, inc, o);
            if (lane >= o) inc += t;
        }
        if (lane == 31) warp_sums[wid] = inc;
        asm volatile("cp.async.bulk.wait_group.read 0;" ::: "memory");
        __syncthreads();
        int woff;
        {
            int ws = warp_sums[lane];
            int winc = ws;
#pragma unroll
            for (int o = 1; o < 32; o <<= 1) {
                int t = __shfl_up_sync(0xffffffffu, winc, o);
                if (lane >= o) winc += t;
            }
            woff = __shfl_sync(0xffffffffu, winc - ws, wid);
        }
        const int e0 = woff + inc - s, e1 = e0 + pc0;
        reinterpret_cast<int2*>(hist)[tid] = make_int2(e0, e1);
        if (tid == 0) hist[BINS_PAD] = P_STAGE;
        for (int k = c2.x; k < pc0; k++) stage[e0 + k] = make_uint2(0u, 0xffffffffu);
        for (int k = c2.y; k < pc1; k++) stage[e1 + k] = make_uint2(0u, 0xffffffffu);
        __syncthreads();
#pragma unroll
        for (int v = 0; v < P_PER / 4; v++) {
            const uint32_t o[4] = {(uint32_t)O[v].x, (uint32_t)O[v].y, (uint32_t)O[v].z, (uint32_t)O[v].w};
            const uint32_t in[4] = {(uint32_t)I[v].x, (uint32_t)I[v].y, (uint32_t)I[v].z, (uint32_t)I[v].w};
            const uint32_t an[4] = {A[v].x & 0xffffu, A[v].x >> 16, A[v].y & 0xffffu, A[v].y >> 16};
#pragma unroll
            for (int u = 0; u < 4; u++) {
                int pos = atomicAdd(&hist[min(o[u] >> NB_LOG, (uint32_t)BINS_PAD)], 1);
                stage[min(pos, P_STAGE - 1)] = make_uint2((in[u] << 5) | (0x1000000u << (o[u] & 7)), an[u] | ((o[u] & 255u) << 16));
            }
        }
        {
            const int nt = tile + gridDim.x;
            if (nt < p.ntiles) {
                const int nbase = nt * p.tile, nn = min(p.tile, p.T - nbase);
#pragma unroll
                for (int v = 0; v < P_PER / 4; v++) O[v] = ld4_guard(p.idx_out + nbase, (v * P_NT + tid) * 4, nn, -1);
            }
        }
        asm volatile("fence.proxy.async.shared::cta;" ::: "memory");
        __syncthreads();
        if (pc0 && g0 + pc0 <= CAPG)
            asm volatile("cp.async.bulk.global.shared::cta.bulk_group [%0], [%1], %2;"
                         :: "l"(g_records + (size_t)(2 * tid) * CAPG + g0), "r"(smem_u32(stage + e0)), "r"(pc0 * 8) : "memory");
        if (pc1 && g1 + pc1 <= CAPG)
            asm volatile("cp.async.bulk.global.shared::cta.bulk_group [%0], [%1], %2;"
                         :: "l"(g_records + (size_t)(2 * tid + 1) * CAPG + g1), "r"(smem_u32(stage + e1)), "r"(pc1 * 8) : "memory");
        asm volatile("cp.async.bulk.commit_group;" ::: "memory");
        reinterpret_cast<int2*>(hist)[tid] = make_int2(0, 0);
        if (tid == 0) hist[BINS_PAD] = 0;
    }
    asm volatile("cp.async.bulk.wait_group 0;" ::: "memory");
}

constexpr int SM_IDX = 0;
constexpr int SM_C01 = SM_IDX + (CAPS + 16) * 4;
constexpr int SM_C2 = SM_C01 + CAPS * 4;
constexpr int SM_OH = SM_C2 + (CAPS + 16) * 2;
constexpr int SM_RING = SM_OH + CAPS;
constexpr int SM_TOTAL = SM_RING + (G_NT / 32) * G_STAGES * 512;

__device__ __forceinline__ uint32_t lds32(uint32_t a) { uint32_t v; asm volatile("ld.shared.u32 %0, [%1];" : "=r"(v) : "r"(a) : "memory"); return v; }
__device__ __forceinline__ uint2 lds64(uint32_t a) { uint2 v; asm volatile("ld.shared.v2.u32 {%0,%1}, [%2];" : "=r"(v.x), "=r"(v.y) : "r"(a) : "memory"); return v; }
__device__ __forceinline__ uint4 lds128(uint32_t a) { uint4 v; asm volatile("ld.shared.v4.u32 {%0,%1,%2,%3}, [%4];" : "=r"(v.x), "=r"(v.y), "=r"(v.z), "=r"(v.w) : "r"(a) : "memory"); return v; }

__global__ void __launch_bounds__(G_NT, G_BLOCKS) k_gather(const __grid_constant__ Params p) {
    extern __shared__ __align__(128) unsigned char smem_raw[];
    uint32_t* sidx = reinterpret_cast<uint32_t*>(smem_raw + SM_IDX);
    uint4* sc01 = reinterpret_cast<uint4*>(smem_raw + SM_C01);
    unsigned short* sc2 = reinterpret_cast<unsigned short*>(smem_raw + SM_C2);
    uint32_t* soh = reinterpret_cast<uint32_t*>(smem_raw + SM_OH);
    __shared__ int cnts[NB + 32];
    __shared__ int gstart[NGRP + 1];
    __shared__ int warp_sums[NB / 32];

    const int tid = threadIdx.x;
    const int lane = tid & 31, wid = tid >> 5;
    const int bin = blockIdx.x;
    const int total = g_cursor[bin];
    const bool ovf = total > CAPG;
    const int n = ovf ? 0 : total;
    if (ovf) slow_bin(&p, bin);

    const uint4* rec = reinterpret_cast<const uint4*>(g_records + (size_t)bin * CAPG) + tid;
    uint4 r[G_PER / 2];
#pragma unroll
    for (int j = 0; j < G_PER / 2; j++) {
        r[j] = make_uint4(0u, 0xffffffffu, 0u, 0xffffffffu);
        if ((j * G_NT + tid) * 2 < n) r[j] = __ldcs(rec + j * G_NT);
    }
    if (tid < NB) cnts[tid] = 0;
    const unsigned short* fq = reinterpret_cast<const unsigned short*>(p.ang_freq);
    const uint32_t f0 = (uint32_t)fq[0] * 0x10001u, f1 = (uint32_t)fq[1] * 0x10001u, f2 = (uint32_t)fq[2] * 0x10001u;
    const uint32_t fmaxp = max(max(f0 & 0x7fff7fffu, f1 & 0x7fff7fffu), f2 & 0x7fff7fffu);
    const uint32_t dkey = NB + lane;
    __syncthreads();
    if (tid == 0) g_cursor[bin] = 0;
#pragma unroll
    for (int j = 0; j < G_PER / 2; j++) {
        atomicAdd(&cnts[min(r[j].y >> 16, dkey)], 1);
        atomicAdd(&cnts[min(r[j].w >> 16, dkey)], 1);
    }
    __syncthreads();
    int c = 0, inc = 0, cp = 0, npad = 0;
    if (tid < NB) {
        c = cnts[tid];
        int gt = c;
        gt += __shfl_xor_sync(0xffffffffu, gt, 1);
        gt += __shfl_xor_sync(0xffffffffu, gt, 2);
        gt += __shfl_xor_sync(0xffffffffu, gt, 4);
        npad = ((gt + 15) & ~15) - gt;
        cp = c + (((lane & 7) == 7) ? npad : 0);
        inc = cp;
#pragma unroll
        for (int o = 1; o < 32; o <<= 1) {
            int t = __shfl_up_sync(0xffffffffu, inc, o);
            if (lane >= o) inc += t;
        }
        if (lane == 31) warp_sums[wid] = inc;
    }
    __syncthreads();
    if (tid < NB) {
        int woff = 0;
#pragma unroll
        for (int w = 0; w < NB / 32; w++) woff += (w < wid) ? warp_sums[w] : 0;
        const int st = woff + inc - cp;
        cnts[tid] = st;
        if ((lane & 7) == 0) gstart[tid >> 3] = st;
        if (tid == NB - 1) gstart[NGRP] = woff + inc;
        if (tid < 32) cnts[NB + tid] = CAPS;
        const int gend = __shfl_sync(0xffffffffu, woff + inc, lane | 7);
        const int k = lane & 7;
        if (k < npad) { sidx[gend - 1 - k] = 0u; sc2[gend - 1 - k] = 0; }
        if (k + 8 < npad) { sidx[gend - 9 - k] = 0u; sc2[gend - 9 - k] = 0; }
    }
    __syncthreads();
#pragma unroll
    for (int j = 0; j < G_PER / 2; j++) {
        {
            const int pos = min(atomicAdd(&cnts[min(r[j].y >> 16, dkey)], 1), CAPS);
            sidx[pos] = r[j].x;
            sc2[pos] = (unsigned short)r[j].y;
        }
        {
            const int pos = min(atomicAdd(&cnts[min(r[j].w >> 16, dkey)], 1), CAPS);
            sidx[pos] = r[j].z;
            sc2[pos] = (unsigned short)r[j].w;
        }
    }
    __syncthreads();
    {
        const int nch = gstart[NGRP] >> 2;
        for (int i = tid; i < nch; i += G_NT) {
            const uint2 a = reinterpret_cast<const uint2*>(sc2)[i];
            const uint4 w = reinterpret_cast<const uint4*>(sidx)[i];
            soh[i] = prmt(prmt(w.x, w.y, 0x0073), prmt(w.z, w.w, 0x0073), 0x5410);
            uint32_t x0 = mul_bf16x2(a.x, f0), x1 = mul_bf16x2(a.y, f0);
            uint32_t x2 = mul_bf16x2(a.x, f1), x3 = mul_bf16x2(a.y, f1);
            uint32_t x4 = mul_bf16x2(a.x, f2), x5 = mul_bf16x2(a.y, f2);
            uint32_t t = mul_bf16x2(__vmaxu2(a.x & 0x7fff7fffu, a.y & 0x7fff7fffu), fmaxp);
            uint4 o; uint2 o2;
            if ((t >> 16) < 0x4300u && (t & 0xffffu) < 0x4300u) {
                o.x = cos_fast_bf16x2(x0); o.y = cos_fast_bf16x2(x1);
                o.z = cos_fast_bf16x2(x2); o.w = cos_fast_bf16x2(x3);
                o2.x = cos_fast_bf16x2(x4); o2.y = cos_fast_bf16x2(x5);
            } else {
                o.x = cos_slow_bf16x2(x0); o.y = cos_slow_bf16x2(x1);
                o.z = cos_slow_bf16x2(x2); o.w = cos_slow_bf16x2(x3);
                o2.x = cos_slow_bf16x2(x4); o2.y = cos_slow_bf16x2(x5);
            }
            sc01[i] = o;
            reinterpret_cast<uint2*>(sc2)[i] = o2;
        }
    }
    __syncthreads();

    const int g = lane >> 2, q = lane & 3;
    constexpr int GPW = NGRP / (G_NT / 32);
    const int grp0 = wid * GPW;
    const int wbeg = gstart[grp0], wend = gstart[grp0 + GPW];
    const unsigned char* mb = reinterpret_cast<const unsigned char*>(p.m);
    const uint32_t sbase = smem_u32(smem_raw);

    const uint32_t ring = sbase + SM_RING + wid * (G_STAGES * 512);
    const int cj = lane >> 1;
    const uint32_t cdst = ring + (uint32_t)((lane & 1) * 256 + (((cj >> 2) * 2 + (cj & 1) + ((cj >> 1) & 1) * 8) * 16));
    const unsigned char* msrc = mb + (lane & 1) * 16;
    const uint32_t lsrc = ring + (uint32_t)(((lane >> 3) & 1) * 256 + ((lane >> 4) * 8 + (lane & 7)) * 16);

    uint32_t iaddr = sbase + SM_IDX + (wbeg + cj) * 4;
    const uint32_t iend = sbase + SM_IDX + wend * 4;
    uint32_t ioff = 0;
#pragma unroll
    for (int k = 0; k < G_STAGES - 1; k++) {
        if (iaddr < iend) cp_async_row(cdst + ioff, msrc, lds32(iaddr));
        cp_async_commit();
        iaddr += 64; ioff += 512;
    }

    uint32_t adown[4], aup[4], asbf[NL][2], arb[2];
    {
        const unsigned short* wd = reinterpret_cast<const unsigned short*>(p.w_down);
        const unsigned short* wu = reinterpret_cast<const unsigned short*>(p.w_up);
        const unsigned short* ws = reinterpret_cast<const unsigned short*>(p.w_sbf);
        const unsigned short* wr = reinterpret_cast<const unsigned short*>(p.w_rbf);
        adown[0] = (uint32_t)wd[(2 * q) * DE + g] | ((uint32_t)wd[(2 * q + 1) * DE + g] << 16);
        adown[1] = (uint32_t)wd[(2 * q) * DE + g + 8] | ((uint32_t)wd[(2 * q + 1) * DE + g + 8] << 16);
        adown[2] = (uint32_t)wd[(2 * q + 8) * DE + g] | ((uint32_t)wd[(2 * q + 9) * DE + g] << 16);
        adown[3] = (uint32_t)wd[(2 * q + 8) * DE + g + 8] | ((uint32_t)wd[(2 * q + 9) * DE + g + 8] << 16);
#pragma unroll
        for (int l = 0; l < NL; l++) {
            asbf[l][0] = (uint32_t)ws[((2 * q) * NL + l) * DE + g] | ((uint32_t)ws[((2 * q + 1) * NL + l) * DE + g] << 16);
            asbf[l][1] = (uint32_t)ws[((2 * q) * NL + l) * DE + g + 8] | ((uint32_t)ws[((2 * q + 1) * NL + l) * DE + g + 8] << 16);
        }
        const int cA = 2 * g, cB = 2 * g + 1;
        aup[0] = (uint32_t)wu[(2 * q) * DE + cA] | ((uint32_t)wu[(2 * q + 1) * DE + cA] << 16);
        aup[1] = (uint32_t)wu[(2 * q) * DE + cB] | ((uint32_t)wu[(2 * q + 1) * DE + cB] << 16);
        aup[2] = (uint32_t)wu[(2 * q + 8) * DE + cA] | ((uint32_t)wu[(2 * q + 9) * DE + cA] << 16);
        aup[3] = (uint32_t)wu[(2 * q + 8) * DE + cB] | ((uint32_t)wu[(2 * q + 9) * DE + cB] << 16);
        arb[0] = (uint32_t)wr[(2 * q) * DE + cA] | ((uint32_t)wr[(2 * q + 1) * DE + cA] << 16);
        arb[1] = (uint32_t)wr[(2 * q) * DE + cB] | ((uint32_t)wr[(2 * q + 1) * DE + cB] << 16);
    }
    const uint32_t cen = reinterpret_cast<const uint32_t*>(p.centers)[q];

    const int ew = bin * NB + grp0 * 8;
    const unsigned short* pdist = reinterpret_cast<const unsigned short*>(p.dist) + ew + g;
    const uint32_t moff0 = (uint32_t)(ew + 2 * q) * 32u + 4u * g;
    const int nleft = p.E - ew;

    uint32_t a01 = sbase + SM_C01 + ((wbeg >> 2) + q) * 16;
    uint32_t a2 = sbase + SM_C2 + ((wbeg >> 2) + q) * 8;
    uint32_t aoh = sbase + SM_OH + ((wbeg >> 2) + q) * 4;
    uint32_t coff = 0;
#pragma unroll 1
    for (int gi = 0; gi < GPW; gi++) {
        const uint32_t aend = sbase + SM_OH + (uint32_t)gstart[grp0 + gi + 1];
        const uint32_t moff = moff0 + gi * 256;
        const bool va = gi * 8 + 2 * q < nleft, vb = gi * 8 + 2 * q + 1 < nleft;
        uint32_t dg = (gi * 8 + g < nleft) ? (uint32_t)pdist[gi * 8] : 0u;
        uint32_t ma = va ? __ldg(reinterpret_cast<const uint32_t*>(mb + moff)) : 0u;
        uint32_t mbv = vb ? __ldg(reinterpret_cast<const uint32_t*>(mb + moff + 32)) : 0u;

        float D[NL][4];
#pragma unroll
        for (int l = 0; l < NL; l++)
#pragma unroll
            for (int c4 = 0; c4 < 4; c4++) D[l][c4] = 0.f;
#pragma unroll 1
        while (aoh < aend) {
            if (iaddr < iend) cp_async_row(cdst + ioff, msrc, lds32(iaddr));
            cp_async_commit();
            iaddr += 64; ioff = (ioff == (G_STAGES - 1) * 512) ? 0 : ioff + 512;
            const uint4 c01 = lds128(a01);
            const uint2 c2 = lds64(a2);
            const uint32_t kb = ((lds32(aoh) >> g) & 0x01010101u) * 0xffu;
            a01 += 64; a2 += 32; aoh += 16;
            const uint32_t k01 = prmt(kb, 0, 0x1100), k23 = prmt(kb, 0, 0x3322);
            cp_async_wait<G_STAGES - 1>();
            __syncwarp();
            uint32_t a[4];
            ldsm_x4_trans(a, lsrc + coff);
            coff = (coff == (G_STAGES - 1) * 512) ? 0 : coff + 512;
            mma16816(D[0], a, c01.x & k01, c01.y & k23);
            mma16816(D[1], a, c01.z & k01, c01.w & k23);
            mma16816(D[2], a, c2.x & k01, c2.y & k23);
        }
        const uint32_t brbf = rbf_bf16x2(dg * 0x10001u, cen);
        float agg[4] = {0.f, 0.f, 0.f, 0.f};
#pragma unroll
        for (int l = 0; l < NL; l++) {
            const uint32_t h0 = movm(pack_bf16(D[l][0], D[l][1]));
            const uint32_t h1 = movm(pack_bf16(D[l][2], D[l][3]));
            float S[4] = {0.f, 0.f, 0.f, 0.f};
            float G[4] = {0.f, 0.f, 0.f, 0.f};
            mma16816(S, adown, h0, h1);
            mma1688(G, asbf[l], brbf);
#pragma unroll
            for (int c4 = 0; c4 < 4; c4++) agg[c4] = fmaf(S[c4], G[c4], agg[c4]);
        }
        if (ovf) {
            const int ea = ew + gi * 8 + 2 * q;
            if (va) {
                float* pa = g_ovf + (size_t)ea * DE + g;
                agg[0] += __ldcg(pa); agg[2] += __ldcg(pa + 8);
                pa[0] = 0.f; pa[8] = 0.f;
            }
            if (vb) {
                float* pb = g_ovf + (size_t)(ea + 1) * DE + g;
                agg[1] += __ldcg(pb); agg[3] += __ldcg(pb + 8);
                pb[0] = 0.f; pb[8] = 0.f;
            }
        }
        {
            const uint32_t h0 = movm(pack_bf16(agg[0], agg[1]));
            const uint32_t h1 = movm(pack_bf16(agg[2], agg[3]));
            float U[4] = {0.f, 0.f, 0.f, 0.f};
            float R[4] = {0.f, 0.f, 0.f, 0.f};
            mma16816(U, aup, h0, h1);
            mma1688(R, arb, brbf);
            uint32_t oa = pack_bf16(fmaf(U[0], R[0], bf16lo(ma)), fmaf(U[2], R[2], bf16hi(ma)));
            uint32_t ob = pack_bf16(fmaf(U[1], R[1], bf16lo(mbv)), fmaf(U[3], R[3], bf16hi(mbv)));
            unsigned char* ob8 = reinterpret_cast<unsigned char*>(p.out);
            if (va) *reinterpret_cast<uint32_t*>(ob8 + moff) = oa;
            if (vb) *reinterpret_cast<uint32_t*>(ob8 + moff + 32) = ob;
        }
    }
}

}

extern "C" void kernel_launch(void* const* d_in, const int* in_sizes, int n_in,
                              void* d_out, int out_size) {
    Params p;
    p.m = (const __nv_bfloat16*)d_in[0];
    p.idx_in = (const int*)d_in[1];
    p.idx_out = (const int*)d_in[2];
    p.dist = (const __nv_bfloat16*)d_in[3];
    p.angle = (const __nv_bfloat16*)d_in[4];
    p.centers = (const __nv_bfloat16*)d_in[5];
    p.ang_freq = (const __nv_bfloat16*)d_in[6];
    p.w_rbf = (const __nv_bfloat16*)d_in[7];
    p.w_sbf = (const __nv_bfloat16*)d_in[8];
    p.w_down = (const __nv_bfloat16*)d_in[9];
    p.w_up = (const __nv_bfloat16*)d_in[10];
    p.out = (__nv_bfloat16*)d_out;
    p.E = in_sizes[3];
    p.T = in_sizes[1];
    p.nbins = (p.E + NB - 1) / NB;

    const int smem1 = P_STAGE * 8 + (BINS_PAD + 4) * 4;
    const int smem2 = SM_TOTAL;
    static int nsm = 0;
    if (!nsm) {
        cudaFuncSetAttribute(k_partition, cudaFuncAttributeMaxDynamicSharedMemorySize, smem1);
        cudaFuncSetAttribute(k_gather, cudaFuncAttributeMaxDynamicSharedMemorySize, smem2);
        int dev = 0;
        cudaGetDevice(&dev);
        cudaDeviceGetAttribute(&nsm, cudaDevAttrMultiProcessorCount, dev);
    }
    long long per_sm = ((long long)p.T + nsm - 1) / nsm;
    int k = (int)((per_sm + P_TILE_MAX - 1) / P_TILE_MAX);
    if (k < 1) k = 1;
    long long tile = ((long long)p.T + (long long)k * nsm - 1) / ((long long)k * nsm);
    tile = (tile + 15) & ~15LL;
    if (tile > P_TILE_MAX) tile = P_TILE_MAX;
    if (tile < 16) tile = 16;
    p.tile = (int)tile;
    p.ntiles = (int)(((long long)p.T + tile - 1) / tile);
    int g1 = p.ntiles < nsm ? p.ntiles : nsm;
    if (g1 > 0) k_partition<<<g1, P_NT, smem1>>>(p);
    k_gather<<<p.nbins, G_NT, smem2>>>(p);
}
```

```cpp
#include <cuda_runtime.h>
#include <cuda_bf16.h>
#include <stdint.h>

namespace {

constexpr int DE = 16;
constexpr int NR = 8;
constexpr int NL = 3;

constexpr int NB_LOG = 8;
constexpr int NB = 1 << NB_LOG;
constexpr int MAX_E = 400000;
constexpr int MAX_BINS = (MAX_E + NB - 1) / NB;
constexpr int BINS_PAD = 2048;
constexpr int CAPG = 5120;

constexpr int P_NT = 1024;
constexpr int P_PER = 16;
constexpr int P_TILE_MAX = P_NT * P_PER;
constexpr int P_STAGE = P_TILE_MAX + 3 * MAX_BINS + 16;

#define CFG_G_NT 256
#define CFG_G_BLOCKS 3
#define CFG_G_STAGES 3
constexpr int G_NT = CFG_G_NT;
constexpr int G_BLOCKS = CFG_G_BLOCKS;
constexpr int G_PER = CAPG / G_NT;
constexpr int NGRP = NB / 8;
constexpr int CAPS = CAPG + NGRP * 16;
constexpr int G_STAGES = CFG_G_STAGES;

__device__ uint2 g_records[(size_t)MAX_BINS * CAPG];
__device__ int g_cursor[BINS_PAD];
__device__ uint4 g_frag[4 * 32];
__device__ float g_ovf[(size_t)MAX_BINS * NB * DE];

__device__ __forceinline__ float bf16r(float x) { return __bfloat162float(__float2bfloat16_rn(x)); }
__device__ __forceinline__ float bf16lo(uint32_t v) { return __uint_as_float(v << 16); }
__device__ __forceinline__ float bf16hi(uint32_t v) { return __uint_as_float(v & 0xffff0000u); }
__device__ __forceinline__ float ldbf(const __nv_bfloat16* p) { return __bfloat162float(*p); }
__device__ __forceinline__ uint32_t smem_u32(const void* p) { return (uint32_t)__cvta_generic_to_shared(p); }

__device__ __forceinline__ uint32_t pack_bf16(float lo, float hi) {
    __nv_bfloat162 v = __floats2bfloat162_rn(lo, hi);
    return *reinterpret_cast<uint32_t*>(&v);
}
__device__ __forceinline__ uint32_t mul_bf16x2(uint32_t a, uint32_t b) {
    __nv_bfloat162 r = __hmul2(*reinterpret_cast<__nv_bfloat162*>(&a), *reinterpret_cast<__nv_bfloat162*>(&b));
    return *reinterpret_cast<uint32_t*>(&r);
}
__device__ __forceinline__ uint32_t sub_bf16x2(uint32_t a, uint32_t b) {
    __nv_bfloat162 r = __hsub2(*reinterpret_cast<__nv_bfloat162*>(&a), *reinterpret_cast<__nv_bfloat162*>(&b));
    return *reinterpret_cast<uint32_t*>(&r);
}
__device__ __forceinline__ uint32_t cos_fast_bf16x2(uint32_t x) {
    return pack_bf16(__cosf(bf16lo(x)), __cosf(bf16hi(x)));
}
__device__ __noinline__ uint32_t cos_slow_bf16x2(uint32_t x) {
    return pack_bf16(cosf(bf16lo(x)), cosf(bf16hi(x)));
}
__device__ __forceinline__ uint32_t rbf_bf16x2(uint32_t dd, uint32_t cc) {
    uint32_t t = sub_bf16x2(dd, cc);
    t = mul_bf16x2(t, t);
    t = mul_bf16x2(t, 0xC120C120u);
    return pack_bf16(__expf(bf16lo(t)), __expf(bf16hi(t)));
}

__device__ __forceinline__ void mma16816(float* d, const uint32_t* a, uint32_t b0, uint32_t b1) {
    asm volatile("mma.sync.aligned.m16n8k16.row.col.f32.bf16.bf16.f32 {%0,%1,%2,%3}, {%4,%5,%6,%7}, {%8,%9}, {%0,%1,%2,%3};"
                 : "+f"(d[0]), "+f"(d[1]), "+f"(d[2]), "+f"(d[3])
                 : "r"(a[0]), "r"(a[1]), "r"(a[2]), "r"(a[3]), "r"(b0), "r"(b1));
}
__device__ __forceinline__ void mma1688(float* d, const uint32_t* a, uint32_t b) {
    asm volatile("mma.sync.aligned.m16n8k8.row.col.f32.bf16.bf16.f32 {%0,%1,%2,%3}, {%4,%5}, {%6}, {%0,%1,%2,%3};"
                 : "+f"(d[0]), "+f"(d[1]), "+f"(d[2]), "+f"(d[3])
                 : "r"(a[0]), "r"(a[1]), "r"(b));
}
__device__ __forceinline__ uint32_t movm(uint32_t a) {
    uint32_t d;
    asm volatile("movmatrix.sync.aligned.m8n8.trans.b16 %0, %1;" : "=r"(d) : "r"(a));
    return d;
}
__device__ __forceinline__ uint32_t prmt(uint32_t a, uint32_t b, uint32_t sel) {
    uint32_t d;
    asm("prmt.b32 %0, %1, %2, %3;" : "=r"(d) : "r"(a), "r"(b), "r"(sel));
    return d;
}
__device__ __forceinline__ void ldsm_x4_trans(uint32_t* r, uint32_t addr) {
    asm volatile("ldmatrix.sync.aligned.m8n8.x4.trans.shared.b16 {%0,%1,%2,%3}, [%4];"
                 : "=r"(r[0]), "=r"(r[1]), "=r"(r[2]), "=r"(r[3]) : "r"(addr) : "memory");
}
__device__ __forceinline__ void cp_async_row(uint32_t dst, const unsigned char* base, uint32_t w) {
    const uint32_t sz = (w >> 24) ? 16u : 0u;
    asm volatile("cp.async.cg.shared.global [%0], [%1], 16, %2;" :: "r"(dst), "l"(base + (w & 0xffffffu)), "r"(sz) : "memory");
}
__device__ __forceinline__ void cp_async_commit() { asm volatile("cp.async.commit_group;" ::: "memory"); }
template <int N> __device__ __forceinline__ void cp_async_wait() { asm volatile("cp.async.wait_group %0;" :: "n"(N) : "memory"); }

struct Params {
    const __nv_bfloat16* m;
    const int* idx_in;
    const int* idx_out;
    const __nv_bfloat16* dist;
    const __nv_bfloat16* angle;
    const __nv_bfloat16* centers;
    const __nv_bfloat16* ang_freq;
    const __nv_bfloat16* w_rbf;
    const __nv_bfloat16* w_sbf;
    const __nv_bfloat16* w_down;
    const __nv_bfloat16* w_up;
    __nv_bfloat16* out;
    int E, T, nbins, ntiles, tile;
};

__device__ __noinline__ void slow_bin(const Params* pp, int bin) {
    const Params& p = *pp;
    for (int t = threadIdx.x; t < p.T; t += blockDim.x) {
        const int out = p.idx_out[t];
        if ((out >> NB_LOG) != bin) continue;
        const int in = p.idx_in[t];
        const float ang = ldbf(p.angle + t);
        float mrow[DE], rb[NR], cb[NL];
        for (int k = 0; k < DE; k++) mrow[k] = ldbf(p.m + (size_t)in * DE + k);
        float d = ldbf(p.dist + out);
        for (int r = 0; r < NR; r++) {
            float u = bf16r(d - ldbf(p.centers + r));
            u = bf16r(u * u);
            u = bf16r(-10.0f * u);
            rb[r] = bf16r(__expf(u));
        }
        for (int l = 0; l < NL; l++) cb[l] = bf16r(cosf(bf16r(ldbf(p.ang_freq + l) * ang)));
        for (int c = 0; c < DE; c++) {
            float md = 0.f, s = 0.f;
            for (int k = 0; k < DE; k++) md = fmaf(mrow[k], ldbf(p.w_down + k * DE + c), md);
            for (int r = 0; r < NR; r++)
                for (int l = 0; l < NL; l++) s = fmaf(rb[r] * cb[l], ldbf(p.w_sbf + (r * NL + l) * DE + c), s);
            atomicAdd(&g_ovf[(size_t)out * DE + c], md * s);
        }
    }
    __threadfence();
}

__device__ __forceinline__ int4 ld4_guard(const int* p, int i, int n, int fill) {
    if (i + 3 < n) return __ldcs(reinterpret_cast<const int4*>(p + i));
    int4 r;
    r.x = (i + 0 < n) ? p[i + 0] : fill;
    r.y = (i + 1 < n) ? p[i + 1] : fill;
    r.z = (i + 2 < n) ? p[i + 2] : fill;
    r.w = fill;
    return r;
}
__device__ __forceinline__ uint2 ld4h_guard(const unsigned short* p, int i, int n) {
    if (i + 3 < n) return __ldcs(reinterpret_cast<const uint2*>(p + i));
    uint32_t a = (i + 0 < n) ? p[i + 0] : 0u, b = (i + 1 < n) ? p[i + 1] : 0u, c = (i + 2 < n) ? p[i + 2] : 0u;
    return make_uint2(a | (b << 16), c);
}

__global__ void __launch_bounds__(P_NT, 1) k_partition(const __grid_constant__ Params p) {
    extern __shared__ __align__(16) unsigned char smem_raw[];
    uint2* stage = reinterpret_cast<uint2*>(smem_raw);
    int* hist = reinterpret_cast<int*>(smem_raw + (size_t)P_STAGE * 8);
    __shared__ int warp_sums[P_NT / 32];
    static_assert(BINS_PAD == 2 * P_NT, "two bins per thread in the scan");

    const int tid = threadIdx.x;
    const int lane = tid & 31, wid = tid >> 5;
    const unsigned short* ang16 = reinterpret_cast<const unsigned short*>(p.angle);

    if (blockIdx.x == 0 && wid == P_NT / 32 - 1) {
        const int g = lane >> 2, q = lane & 3;
        const unsigned short* wd = reinterpret_cast<const unsigned short*>(p.w_down);
        const unsigned short* wu = reinterpret_cast<const unsigned short*>(p.w_up);
        const unsigned short* ws = reinterpret_cast<const unsigned short*>(p.w_sbf);
        const unsigned short* wr = reinterpret_cast<const unsigned short*>(p.w_rbf);
        uint4 t;
        t.x = (uint32_t)wd[(2 * q) * DE + g] | ((uint32_t)wd[(2 * q + 1) * DE + g] << 16);
        t.y = (uint32_t)wd[(2 * q) * DE + g + 8] | ((uint32_t)wd[(2 * q + 1) * DE + g + 8] << 16);
        t.z = (uint32_t)wd[(2 * q + 8) * DE + g] | ((uint32_t)wd[(2 * q + 9) * DE + g] << 16);
        t.w = (uint32_t)wd[(2 * q + 8) * DE + g + 8] | ((uint32_t)wd[(2 * q + 9) * DE + g + 8] << 16);
        g_frag[lane] = t;
        const int cA = 2 * g, cB = 2 * g + 1;
        t.x = (uint32_t)wu[(2 * q) * DE + cA] | ((uint32_t)wu[(2 * q + 1) * DE + cA] << 16);
        t.y = (uint32_t)wu[(2 * q) * DE + cB] | ((uint32_t)wu[(2 * q + 1) * DE + cB] << 16);
        t.z = (uint32_t)wu[(2 * q + 8) * DE + cA] | ((uint32_t)wu[(2 * q + 9) * DE + cA] << 16);
        t.w = (uint32_t)wu[(2 * q + 8) * DE + cB] | ((uint32_t)wu[(2 * q + 9) * DE + cB] << 16);
        g_frag[32 + lane] = t;
        uint32_t sb[NL][2];
#pragma unroll
        for (int l = 0; l < NL; l++) {
            sb[l][0] = (uint32_t)ws[((2 * q) * NL + l) * DE + g] | ((uint32_t)ws[((2 * q + 1) * NL + l) * DE + g] << 16);
            sb[l][1] = (uint32_t)ws[((2 * q) * NL + l) * DE + g + 8] | ((uint32_t)ws[((2 * q + 1) * NL + l) * DE + g + 8] << 16);
        }
        g_frag[64 + lane] = make_uint4(sb[0][0], sb[0][1], sb[1][0], sb[1][1]);
        t.x = sb[2][0]; t.y = sb[2][1];
        t.z = (uint32_t)wr[(2 * q) * DE + cA] | ((uint32_t)wr[(2 * q + 1) * DE + cA] << 16);
        t.w = (uint32_t)wr[(2 * q) * DE + cB] | ((uint32_t)wr[(2 * q + 1) * DE + cB] << 16);
        g_frag[96 + lane] = t;
    }

    int4 O[P_PER / 4];
    int tile = blockIdx.x;
    if (tile < p.ntiles) {
        const int base = tile * p.tile, n = min(p.tile, p.T - base);
#pragma unroll
        for (int v = 0; v < P_PER / 4; v++) O[v] = ld4_guard(p.idx_out + base, (v * P_NT + tid) * 4, n, -1);
    }
    reinterpret_cast<int2*>(hist)[tid] = make_int2(0, 0);
    if (tid == 0) hist[BINS_PAD] = 0;
    for (; tile < p.ntiles; tile += gridDim.x) {
        const int base = tile * p.tile, n = min(p.tile, p.T - base);
        __syncthreads();
#pragma unroll
        for (int v = 0; v < P_PER / 4; v++) {
            atomicAdd(&hist[min((uint32_t)O[v].x >> NB_LOG, (uint32_t)BINS_PAD)], 1);
            atomicAdd(&hist[min((uint32_t)O[v].y >> NB_LOG, (uint32_t)BINS_PAD)], 1);
            atomicAdd(&hist[min((uint32_t)O[v].z >> NB_LOG, (uint32_t)BINS_PAD)], 1);
            atomicAdd(&hist[min((uint32_t)O[v].w >> NB_LOG, (uint32_t)BINS_PAD)], 1);
        }
        int4 I[P_PER / 4];
        uint2 A[P_PER / 4];
#pragma unroll
        for (int v = 0; v < P_PER / 4; v++) {
            I[v] = ld4_guard(p.idx_in + base, (v * P_NT + tid) * 4, n, 0);
            A[v] = ld4h_guard(ang16 + base, (v * P_NT + tid) * 4, n);
        }
        __syncthreads();
        const int2 c2 = reinterpret_cast<int2*>(hist)[tid];
        const int pc0 = (c2.x + 3) & ~3, pc1 = (c2.y + 3) & ~3;
        int g0 = 0, g1 = 0;
        if (pc0) g0 = atomicAdd(&g_cursor[2 * tid], pc0);
        if (pc1) g1 = atomicAdd(&g_cursor[2 * tid + 1], pc1);
        const int s = pc0 + pc1;
        int inc = s;
#pragma unroll
        for (int o = 1; o < 32; o <<= 1) {
            int t = __shfl_up_sync(0xffffffffu, inc, o);
            if (lane >= o) inc += t;
        }
        if (lane == 31) warp_sums[wid] = inc;
        asm volatile("cp.async.bulk.wait_group.read 0;" ::: "memory");
        __syncthreads();
        int woff;
        {
            int ws = warp_sums[lane];
            int winc = ws;
#pragma unroll
            for (int o = 1; o < 32; o <<= 1) {
                int t = __shfl_up_sync(0xffffffffu, winc, o);
                if (lane >= o) winc += t;
            }
            woff = __shfl_sync(0xffffffffu, winc - ws, wid);
        }
        const int e0 = woff + inc - s, e1 = e0 + pc0;
        reinterpret_cast<int2*>(hist)[tid] = make_int2(e0, e1);
        if (tid == 0) hist[BINS_PAD] = P_STAGE;
        for (int k = c2.x; k < pc0; k++) stage[e0 + k] = make_uint2(0u, 0xffffffffu);
        for (int k = c2.y; k < pc1; k++) stage[e1 + k] = make_uint2(0u, 0xffffffffu);
        __syncthreads();
#pragma unroll
        for (int v = 0; v < P_PER / 4; v++) {
            const uint32_t o[4] = {(uint32_t)O[v].x, (uint32_t)O[v].y, (uint32_t)O[v].z, (uint32_t)O[v].w};
            const uint32_t in[4] = {(uint32_t)I[v].x, (uint32_t)I[v].y, (uint32_t)I[v].z, (uint32_t)I[v].w};
            const uint32_t an[4] = {A[v].x & 0xffffu, A[v].x >> 16, A[v].y & 0xffffu, A[v].y >> 16};
#pragma unroll
            for (int u = 0; u < 4; u++) {
                int pos = atomicAdd(&hist[min(o[u] >> NB_LOG, (uint32_t)BINS_PAD)], 1);
                stage[min(pos, P_STAGE - 1)] = make_uint2((in[u] << 5) | (0x1000000u << (o[u] & 7)), an[u] | ((o[u] & 255u) << 16));
            }
        }
        {
            const int nt = tile + gridDim.x;
            if (nt < p.ntiles) {
                const int nbase = nt * p.tile, nn = min(p.tile, p.T - nbase);
#pragma unroll
                for (int v = 0; v < P_PER / 4; v++) O[v] = ld4_guard(p.idx_out + nbase, (v * P_NT + tid) * 4, nn, -1);
            }
        }
        asm volatile("fence.proxy.async.shared::cta;" ::: "memory");
        __syncthreads();
        if (pc0 && g0 + pc0 <= CAPG)
            asm volatile("cp.async.bulk.global.shared::cta.bulk_group [%0], [%1], %2;"
                         :: "l"(g_records + (size_t)(2 * tid) * CAPG + g0), "r"(smem_u32(stage + e0)), "r"(pc0 * 8) : "memory");
        if (pc1 && g1 + pc1 <= CAPG)
            asm volatile("cp.async.bulk.global.shared::cta.bulk_group [%0], [%1], %2;"
                         :: "l"(g_records + (size_t)(2 * tid + 1) * CAPG + g1), "r"(smem_u32(stage + e1)), "r"(pc1 * 8) : "memory");
        asm volatile("cp.async.bulk.commit_group;" ::: "memory");
        reinterpret_cast<int2*>(hist)[tid] = make_int2(0, 0);
        if (tid == 0) hist[BINS_PAD] = 0;
    }
    asm volatile("cp.async.bulk.wait_group 0;" ::: "memory");
}

constexpr int SM_IDX = 0;
constexpr int SM_C01 = SM_IDX + (CAPS + 16) * 4;
constexpr int SM_C2 = SM_C01 + CAPS * 4;
constexpr int SM_OH = SM_C2 + (CAPS + 16) * 2;
constexpr int SM_RING = SM_OH + CAPS;
constexpr int SM_TOTAL = SM_RING + (G_NT / 32) * G_STAGES * 512;

__device__ __forceinline__ uint32_t lds32(uint32_t a) { uint32_t v; asm volatile("ld.shared.u32 %0, [%1];" : "=r"(v) : "r"(a) : "memory"); return v; }
__device__ __forceinline__ uint2 lds64(uint32_t a) { uint2 v; asm volatile("ld.shared.v2.u32 {%0,%1}, [%2];" : "=r"(v.x), "=r"(v.y) : "r"(a) : "memory"); return v; }
__device__ __forceinline__ uint4 lds128(uint32_t a) { uint4 v; asm volatile("ld.shared.v4.u32 {%0,%1,%2,%3}, [%4];" : "=r"(v.x), "=r"(v.y), "=r"(v.z), "=r"(v.w) : "r"(a) : "memory"); return v; }

__global__ void __launch_bounds__(G_NT, G_BLOCKS) k_gather(const __grid_constant__ Params p) {
    extern __shared__ __align__(128) unsigned char smem_raw[];
    uint32_t* sidx = reinterpret_cast<uint32_t*>(smem_raw + SM_IDX);
    uint4* sc01 = reinterpret_cast<uint4*>(smem_raw + SM_C01);
    unsigned short* sc2 = reinterpret_cast<unsigned short*>(smem_raw + SM_C2);
    uint32_t* soh = reinterpret_cast<uint32_t*>(smem_raw + SM_OH);
    __shared__ int cnts[NB + 32];
    __shared__ int gstart[NGRP + 1];
    __shared__ int warp_sums[NB / 32];

    const int tid = threadIdx.x;
    const int lane = tid & 31, wid = tid >> 5;
    const int bin = blockIdx.x;
    const int total = g_cursor[bin];
    const bool ovf = total > CAPG;
    const int n = ovf ? 0 : total;
    if (ovf) slow_bin(&p, bin);

    const uint4* rec = reinterpret_cast<const uint4*>(g_records + (size_t)bin * CAPG) + tid;
    uint4 r[G_PER / 2];
#pragma unroll
    for (int j = 0; j < G_PER / 2; j++) {
        r[j] = make_uint4(0u, 0xffffffffu, 0u, 0xffffffffu);
        if ((j * G_NT + tid) * 2 < n) r[j] = __ldcs(rec + j * G_NT);
    }
    if (tid < NB) cnts[tid] = 0;
    const unsigned short* fq = reinterpret_cast<const unsigned short*>(p.ang_freq);
    const uint32_t f0 = (uint32_t)fq[0] * 0x10001u, f1 = (uint32_t)fq[1] * 0x10001u, f2 = (uint32_t)fq[2] * 0x10001u;
    const uint32_t fmaxp = max(max(f0 & 0x7fff7fffu, f1 & 0x7fff7fffu), f2 & 0x7fff7fffu);
    const uint32_t dkey = NB + lane;
    __syncthreads();
    if (tid == 0) g_cursor[bin] = 0;
#pragma unroll
    for (int j = 0; j < G_PER / 2; j++) {
        atomicAdd(&cnts[min(r[j].y >> 16, dkey)], 1);
        atomicAdd(&cnts[min(r[j].w >> 16, dkey)], 1);
    }
    __syncthreads();
    int c = 0, inc = 0, cp = 0, npad = 0;
    if (tid < NB) {
        c = cnts[tid];
        int gt = c;
        gt += __shfl_xor_sync(0xffffffffu, gt, 1);
        gt += __shfl_xor_sync(0xffffffffu, gt, 2);
        gt += __shfl_xor_sync(0xffffffffu, gt, 4);
        npad = ((gt + 15) & ~15) - gt;
        cp = c + (((lane & 7) == 7) ? npad : 0);
        inc = cp;
#pragma unroll
        for (int o = 1; o < 32; o <<= 1) {
            int t = __shfl_up_sync(0xffffffffu, inc, o);
            if (lane >= o) inc += t;
        }
        if (lane == 31) warp_sums[wid] = inc;
    }
    __syncthreads();
    if (tid < NB) {
        int woff = 0;
#pragma unroll
        for (int w = 0; w < NB / 32; w++) woff += (w < wid) ? warp_sums[w] : 0;
        const int st = woff + inc - cp;
        cnts[tid] = st;
        if ((lane & 7) == 0) gstart[tid >> 3] = st;
        if (tid == NB - 1) gstart[NGRP] = woff + inc;
        if (tid < 32) cnts[NB + tid] = CAPS;
        const int gend = __shfl_sync(0xffffffffu, woff + inc, lane | 7);
        const int k = lane & 7;
        if (k < npad) { sidx[gend - 1 - k] = 0u; sc2[gend - 1 - k] = 0; }
        if (k + 8 < npad) { sidx[gend - 9 - k] = 0u; sc2[gend - 9 - k] = 0; }
    }
    __syncthreads();
#pragma unroll
    for (int j = 0; j < G_PER / 2; j++) {
        {
            const int pos = min(atomicAdd(&cnts[min(r[j].y >> 16, dkey)], 1), CAPS);
            sidx[pos] = r[j].x;
            sc2[pos] = (unsigned short)r[j].y;
        }
        {
            const int pos = min(atomicAdd(&cnts[min(r[j].w >> 16, dkey)], 1), CAPS);
            sidx[pos] = r[j].z;
            sc2[pos] = (unsigned short)r[j].w;
        }
    }
    __syncthreads();
    {
        const int nch = gstart[NGRP] >> 2;
        for (int i = tid; i < nch; i += G_NT) {
            const uint2 a = reinterpret_cast<const uint2*>(sc2)[i];
            const uint4 w = reinterpret_cast<const uint4*>(sidx)[i];
            soh[i] = prmt(prmt(w.x, w.y, 0x0073), prmt(w.z, w.w, 0x0073), 0x5410);
            uint32_t x0 = mul_bf16x2(a.x, f0), x1 = mul_bf16x2(a.y, f0);
            uint32_t x2 = mul_bf16x2(a.x, f1), x3 = mul_bf16x2(a.y, f1);
            uint32_t x4 = mul_bf16x2(a.x, f2), x5 = mul_bf16x2(a.y, f2);
            uint32_t t = mul_bf16x2(__vmaxu2(a.x & 0x7fff7fffu, a.y & 0x7fff7fffu), fmaxp);
            uint4 o; uint2 o2;
            if ((t >> 16) < 0x4300u && (t & 0xffffu) < 0x4300u) {
                o.x = cos_fast_bf16x2(x0); o.y = cos_fast_bf16x2(x1);
                o.z = cos_fast_bf16x2(x2); o.w = cos_fast_bf16x2(x3);
                o2.x = cos_fast_bf16x2(x4); o2.y = cos_fast_bf16x2(x5);
            } else {
                o.x = cos_slow_bf16x2(x0); o.y = cos_slow_bf16x2(x1);
                o.z = cos_slow_bf16x2(x2); o.w = cos_slow_bf16x2(x3);
                o2.x = cos_slow_bf16x2(x4); o2.y = cos_slow_bf16x2(x5);
            }
            sc01[i] = o;
            reinterpret_cast<uint2*>(sc2)[i] = o2;
        }
    }
    __syncthreads();

    const int g = lane >> 2, q = lane & 3;
    constexpr int GPW = NGRP / (G_NT / 32);
    const int grp0 = wid * GPW;
    const int wbeg = gstart[grp0], wend = gstart[grp0 + GPW];
    const unsigned char* mb = reinterpret_cast<const unsigned char*>(p.m);
    const uint32_t sbase = smem_u32(smem_raw);

    const uint32_t ring = sbase + SM_RING + wid * (G_STAGES * 512);
    const int cj = lane >> 1;
    const int crow = (cj >> 2) * 2 + (cj & 1) + ((cj >> 1) & 1) * 8;
    const uint32_t cdst = ring + (uint32_t)(crow * 32 + (((lane ^ (crow >> 2)) & 1) * 16));
    const unsigned char* msrc = mb + (lane & 1) * 16;
    const int lrow = (lane >> 4) * 8 + (lane & 7);
    const uint32_t lsrc = ring + (uint32_t)(lrow * 32 + ((((lane >> 3) ^ (lrow >> 2)) & 1) * 16));

    uint32_t iaddr = sbase + SM_IDX + (wbeg + cj) * 4;
    const uint32_t iend = sbase + SM_IDX + wend * 4;
    uint32_t ioff = 0;
#pragma unroll
    for (int k = 0; k < G_STAGES - 1; k++) {
        if (iaddr < iend) cp_async_row(cdst + ioff, msrc, lds32(iaddr));
        cp_async_commit();
        iaddr += 64; ioff += 512;
    }

    uint32_t adown[4], aup[4], asbf[NL][2], arb[2];
    {
        const uint4* fr = reinterpret_cast<const uint4*>(g_frag) + lane;
        const uint4 t0 = __ldg(fr), t1 = __ldg(fr + 32), t2 = __ldg(fr + 64), t3 = __ldg(fr + 96);
        adown[0] = t0.x; adown[1] = t0.y; adown[2] = t0.z; adown[3] = t0.w;
        aup[0] = t1.x; aup[1] = t1.y; aup[2] = t1.z; aup[3] = t1.w;
        asbf[0][0] = t2.x; asbf[0][1] = t2.y; asbf[1][0] = t2.z; asbf[1][1] = t2.w;
        asbf[2][0] = t3.x; asbf[2][1] = t3.y; arb[0] = t3.z; arb[1] = t3.w;
    }
    const uint32_t cen = reinterpret_cast<const uint32_t*>(p.centers)[q];

    const int ew = bin * NB + grp0 * 8;
    const unsigned short* pdist = reinterpret_cast<const unsigned short*>(p.dist) + ew + g;
    const uint32_t moff0 = (uint32_t)(ew + 2 * q) * 32u + 4u * g;
    const int nleft = p.E - ew;

    uint32_t a01 = sbase + SM_C01 + ((wbeg >> 2) + q) * 16;
    uint32_t a2 = sbase + SM_C2 + ((wbeg >> 2) + q) * 8;
    uint32_t aoh = sbase + SM_OH + ((wbeg >> 2) + q) * 4;
    uint32_t coff = 0;
#pragma unroll 1
    for (int gi = 0; gi < GPW; gi++) {
        const uint32_t aend = sbase + SM_OH + (uint32_t)gstart[grp0 + gi + 1];
        const uint32_t moff = moff0 + gi * 256;
        const bool va = gi * 8 + 2 * q < nleft, vb = gi * 8 + 2 * q + 1 < nleft;
        uint32_t dg = (gi * 8 + g < nleft) ? (uint32_t)pdist[gi * 8] : 0u;
        uint32_t ma = va ? __ldg(reinterpret_cast<const uint32_t*>(mb + moff)) : 0u;
        uint32_t mbv = vb ? __ldg(reinterpret_cast<const uint32_t*>(mb + moff + 32)) : 0u;

        float D[NL][4];
#pragma unroll
        for (int l = 0; l < NL; l++)
#pragma unroll
            for (int c4 = 0; c4 < 4; c4++) D[l][c4] = 0.f;
#pragma unroll 1
        while (aoh < aend) {
            if (iaddr < iend) cp_async_row(cdst + ioff, msrc, lds32(iaddr));
            cp_async_commit();
            iaddr += 64; ioff = (ioff == (G_STAGES - 1) * 512) ? 0 : ioff + 512;
            const uint4 c01 = lds128(a01);
            const uint2 c2 = lds64(a2);
            const uint32_t kb = ((lds32(aoh) >> g) & 0x01010101u) * 0xffu;
            a01 += 64; a2 += 32; aoh += 16;
            const uint32_t k01 = prmt(kb, 0, 0x1100), k23 = prmt(kb, 0, 0x3322);
            cp_async_wait<G_STAGES - 1>();
            __syncwarp();
            uint32_t a[4];
            ldsm_x4_trans(a, lsrc + coff);
            coff = (coff == (G_STAGES - 1) * 512) ? 0 : coff + 512;
            mma16816(D[0], a, c01.x & k01, c01.y & k23);
            mma16816(D[1], a, c01.z & k01, c01.w & k23);
            mma16816(D[2], a, c2.x & k01, c2.y & k23);
        }
        const uint32_t brbf = rbf_bf16x2(dg * 0x10001u, cen);
        float agg[4] = {0.f, 0.f, 0.f, 0.f};
#pragma unroll
        for (int l = 0; l < NL; l++) {
            const uint32_t h0 = movm(pack_bf16(D[l][0], D[l][1]));
            const uint32_t h1 = movm(pack_bf16(D[l][2], D[l][3]));
            float S[4] = {0.f, 0.f, 0.f, 0.f};
            float G[4] = {0.f, 0.f, 0.f, 0.f};
            mma16816(S, adown, h0, h1);
            mma1688(G, asbf[l], brbf);
#pragma unroll
            for (int c4 = 0; c4 < 4; c4++) agg[c4] = fmaf(S[c4], G[c4], agg[c4]);
        }
        if (ovf) {
            const int ea = ew + gi * 8 + 2 * q;
            if (va) {
                float* pa = g_ovf + (size_t)ea * DE + g;
                agg[0] += __ldcg(pa); agg[2] += __ldcg(pa + 8);
                pa[0] = 0.f; pa[8] = 0.f;
            }
            if (vb) {
                float* pb = g_ovf + (size_t)(ea + 1) * DE + g;
                agg[1] += __ldcg(pb); agg[3] += __ldcg(pb + 8);
                pb[0] = 0.f; pb[8] = 0.f;
            }
        }
        {
            const uint32_t h0 = movm(pack_bf16(agg[0], agg[1]));
            const uint32_t h1 = movm(pack_bf16(agg[2], agg[3]));
            float U[4] = {0.f, 0.f, 0.f, 0.f};
            float R[4] = {0.f, 0.f, 0.f, 0.f};
            mma16816(U, aup, h0, h1);
            mma1688(R, arb, brbf);
            uint32_t oa = pack_bf16(fmaf(U[0], R[0], bf16lo(ma)), fmaf(U[2], R[2], bf16hi(ma)));
            uint32_t ob = pack_bf16(fmaf(U[1], R[1], bf16lo(mbv)), fmaf(U[3], R[3], bf16hi(mbv)));
            unsigned char* ob8 = reinterpret_cast<unsigned char*>(p.out);
            if (va) *reinterpret_cast<uint32_t*>(ob8 + moff) = oa;
            if (vb) *reinterpret_cast<uint32_t*>(ob8 + moff + 32) = ob;
        }
    }
}

}

extern "C" void kernel_launch(void* const* d_in, const int* in_sizes, int n_in,
                              void* d_out, int out_size) {
    Params p;
    p.m = (const __nv_bfloat16*)d_in[0];
    p.idx_in = (const int*)d_in[1];
    p.idx_out = (const int*)d_in[2];
    p.dist = (const __nv_bfloat16*)d_in[3];
    p.angle = (const __nv_bfloat16*)d_in[4];
    p.centers = (const __nv_bfloat16*)d_in[5];
    p.ang_freq = (const __nv_bfloat16*)d_in[6];
    p.w_rbf = (const __nv_bfloat16*)d_in[7];
    p.w_sbf = (const __nv_bfloat16*)d_in[8];
    p.w_down = (const __nv_bfloat16*)d_in[9];
    p.w_up = (const __nv_bfloat16*)d_in[10];
    p.out = (__nv_bfloat16*)d_out;
    p.E = in_sizes[3];
    p.T = in_sizes[1];
    p.nbins = (p.E + NB - 1) / NB;

    const int smem1 = P_STAGE * 8 + (BINS_PAD + 4) * 4;
    const int smem2 = SM_TOTAL;
    static int nsm = 0;
    if (!nsm) {
        cudaFuncSetAttribute(k_partition, cudaFuncAttributeMaxDynamicSharedMemorySize, smem1);
        cudaFuncSetAttribute(k_gather, cudaFuncAttributeMaxDynamicSharedMemorySize, smem2);
        int dev = 0;
        cudaGetDevice(&dev);
        cudaDeviceGetAttribute(&nsm, cudaDevAttrMultiProcessorCount, dev);
    }
    long long per_sm = ((long long)p.T + nsm - 1) / nsm;
    int k = (int)((per_sm + P_TILE_MAX - 1) / P_TILE_MAX);
    if (k < 1) k = 1;
    long long tile = ((long long)p.T + (long long)k * nsm - 1) / ((long long)k * nsm);
    tile = (tile + 15) & ~15LL;
    if (tile > P_TILE_MAX) tile = P_TILE_MAX;
    if (tile < 16) tile = 16;
    p.tile = (int)tile;
    p.ntiles = (int)(((long long)p.T + tile - 1) / tile);
    int g1 = p.ntiles < nsm ? p.ntiles : nsm;
    if (g1 < 1) g1 = 1;
    k_partition<<<g1, P_NT, smem1>>>(p);
    k_gather<<<p.nbins, G_NT, smem2>>>(p);
}
```

```cpp
#include <cuda_runtime.h>
#include <cuda_bf16.h>
#include <stdint.h>

namespace {

constexpr int DE = 16;
constexpr int NR = 8;
constexpr int NL = 3;

constexpr int NB_LOG = 8;
constexpr int NB = 1 << NB_LOG;
constexpr int MAX_E = 400000;
constexpr int MAX_BINS = (MAX_E + NB - 1) / NB;
constexpr int BINS_PAD = 2048;
constexpr int CAPG = 5120;

constexpr int P_NT = 1024;
constexpr int P_PER = 16;
constexpr int P_TILE_MAX = P_NT * P_PER;
constexpr int P_STAGE = P_TILE_MAX + 3 * MAX_BINS + 16;

#define CFG_G_NT 256
#define CFG_G_BLOCKS 3
#define CFG_G_STAGES 3
constexpr int G_NT = CFG_G_NT;
constexpr int G_BLOCKS = CFG_G_BLOCKS;
constexpr int G_PER = CAPG / G_NT;
constexpr int NGRP = NB / 8;
constexpr int CAPS = CAPG + NGRP * 16;
constexpr int G_STAGES = CFG_G_STAGES;

__device__ uint2 g_records[(size_t)MAX_BINS * CAPG];
__device__ int g_cursor[BINS_PAD];
__device__ uint4 g_frag[4 * 32];
__device__ float g_ovf[(size_t)MAX_BINS * NB * DE];

__device__ __forceinline__ float bf16r(float x) { return __bfloat162float(__float2bfloat16_rn(x)); }
__device__ __forceinline__ float bf16lo(uint32_t v) { return __uint_as_float(v << 16); }
__device__ __forceinline__ float bf16hi(uint32_t v) { return __uint_as_float(v & 0xffff0000u); }
__device__ __forceinline__ float ldbf(const __nv_bfloat16* p) { return __bfloat162float(*p); }
__device__ __forceinline__ uint32_t smem_u32(const void* p) { return (uint32_t)__cvta_generic_to_shared(p); }

__device__ __forceinline__ uint32_t pack_bf16(float lo, float hi) {
    __nv_bfloat162 v = __floats2bfloat162_rn(lo, hi);
    return *reinterpret_cast<uint32_t*>(&v);
}
__device__ __forceinline__ uint32_t mul_bf16x2(uint32_t a, uint32_t b) {
    __nv_bfloat162 r = __hmul2(*reinterpret_cast<__nv_bfloat162*>(&a), *reinterpret_cast<__nv_bfloat162*>(&b));
    return *reinterpret_cast<uint32_t*>(&r);
}
__device__ __forceinline__ uint32_t sub_bf16x2(uint32_t a, uint32_t b) {
    __nv_bfloat162 r = __hsub2(*reinterpret_cast<__nv_bfloat162*>(&a), *reinterpret_cast<__nv_bfloat162*>(&b));
    return *reinterpret_cast<uint32_t*>(&r);
}
__device__ __forceinline__ uint32_t cos_fast_bf16x2(uint32_t x) {
    return pack_bf16(__cosf(bf16lo(x)), __cosf(bf16hi(x)));
}
__device__ __noinline__ uint32_t cos_slow_bf16x2(uint32_t x) {
    return pack_bf16(cosf(bf16lo(x)), cosf(bf16hi(x)));
}
__device__ __forceinline__ uint32_t rbf_bf16x2(uint32_t dd, uint32_t cc) {
    uint32_t t = sub_bf16x2(dd, cc);
    t = mul_bf16x2(t, t);
    t = mul_bf16x2(t, 0xC120C120u);
    return pack_bf16(__expf(bf16lo(t)), __expf(bf16hi(t)));
}

__device__ __forceinline__ void mma16816(float* d, const uint32_t* a, uint32_t b0, uint32_t b1) {
    asm volatile("mma.sync.aligned.m16n8k16.row.col.f32.bf16.bf16.f32 {%0,%1,%2,%3}, {%4,%5,%6,%7}, {%8,%9}, {%0,%1,%2,%3};"
                 : "+f"(d[0]), "+f"(d[1]), "+f"(d[2]), "+f"(d[3])
                 : "r"(a[0]), "r"(a[1]), "r"(a[2]), "r"(a[3]), "r"(b0), "r"(b1));
}
__device__ __forceinline__ void mma1688(float* d, const uint32_t* a, uint32_t b) {
    asm volatile("mma.sync.aligned.m16n8k8.row.col.f32.bf16.bf16.f32 {%0,%1,%2,%3}, {%4,%5}, {%6}, {%0,%1,%2,%3};"
                 : "+f"(d[0]), "+f"(d[1]), "+f"(d[2]), "+f"(d[3])
                 : "r"(a[0]), "r"(a[1]), "r"(b));
}
__device__ __forceinline__ uint32_t movm(uint32_t a) {
    uint32_t d;
    asm volatile("movmatrix.sync.aligned.m8n8.trans.b16 %0, %1;" : "=r"(d) : "r"(a));
    return d;
}
__device__ __forceinline__ uint32_t prmt(uint32_t a, uint32_t b, uint32_t sel) {
    uint32_t d;
    asm("prmt.b32 %0, %1, %2, %3;" : "=r"(d) : "r"(a), "r"(b), "r"(sel));
    return d;
}
__device__ __forceinline__ void ldsm_x4_trans(uint32_t* r, uint32_t addr) {
    asm volatile("ldmatrix.sync.aligned.m8n8.x4.trans.shared.b16 {%0,%1,%2,%3}, [%4];"
                 : "=r"(r[0]), "=r"(r[1]), "=r"(r[2]), "=r"(r[3]) : "r"(addr) : "memory");
}
__device__ __forceinline__ void cp_async_row(uint32_t dst, const unsigned char* base, uint32_t w) {
    const uint32_t sz = (w >> 24) ? 16u : 0u;
    asm volatile("cp.async.cg.shared.global [%0], [%1], 16, %2;" :: "r"(dst), "l"(base + (w & 0xffffffu)), "r"(sz) : "memory");
}
__device__ __forceinline__ void cp_async_commit() { asm volatile("cp.async.commit_group;" ::: "memory"); }
template <int N> __device__ __forceinline__ void cp_async_wait() { asm volatile("cp.async.wait_group %0;" :: "n"(N) : "memory"); }

struct Params {
    const __nv_bfloat16* m;
    const int* idx_in;
    const int* idx_out;
    const __nv_bfloat16* dist;
    const __nv_bfloat16* angle;
    const __nv_bfloat16* centers;
    const __nv_bfloat16* ang_freq;
    const __nv_bfloat16* w_rbf;
    const __nv_bfloat16* w_sbf;
    const __nv_bfloat16* w_down;
    const __nv_bfloat16* w_up;
    __nv_bfloat16* out;
    int E, T, nbins, ntiles, tile;
};

__device__ __noinline__ void slow_bin(const Params* pp, int bin) {
    const Params& p = *pp;
    for (int t = threadIdx.x; t < p.T; t += blockDim.x) {
        const int out = p.idx_out[t];
        if ((out >> NB_LOG) != bin) continue;
        const int in = p.idx_in[t];
        const float ang = ldbf(p.angle + t);
        float mrow[DE], rb[NR], cb[NL];
        for (int k = 0; k < DE; k++) mrow[k] = ldbf(p.m + (size_t)in * DE + k);
        float d = ldbf(p.dist + out);
        for (int r = 0; r < NR; r++) {
            float u = bf16r(d - ldbf(p.centers + r));
            u = bf16r(u * u);
            u = bf16r(-10.0f * u);
            rb[r] = bf16r(__expf(u));
        }
        for (int l = 0; l < NL; l++) cb[l] = bf16r(cosf(bf16r(ldbf(p.ang_freq + l) * ang)));
        for (int c = 0; c < DE; c++) {
            float md = 0.f, s = 0.f;
            for (int k = 0; k < DE; k++) md = fmaf(mrow[k], ldbf(p.w_down + k * DE + c), md);
            for (int r = 0; r < NR; r++)
                for (int l = 0; l < NL; l++) s = fmaf(rb[r] * cb[l], ldbf(p.w_sbf + (r * NL + l) * DE + c), s);
            atomicAdd(&g_ovf[(size_t)out * DE + c], md * s);
        }
    }
    __threadfence();
}

__device__ __forceinline__ int4 ld4_guard(const int* p, int i, int n, int fill) {
    if (i + 3 < n) return __ldcs(reinterpret_cast<const int4*>(p + i));
    int4 r;
    r.x = (i + 0 < n) ? p[i + 0] : fill;
    r.y = (i + 1 < n) ? p[i + 1] : fill;
    r.z = (i + 2 < n) ? p[i + 2] : fill;
    r.w = fill;
    return r;
}
__device__ __forceinline__ uint2 ld4h_guard(const unsigned short* p, int i, int n) {
    if (i + 3 < n) return __ldcs(reinterpret_cast<const uint2*>(p + i));
    uint32_t a = (i + 0 < n) ? p[i + 0] : 0u, b = (i + 1 < n) ? p[i + 1] : 0u, c = (i + 2 < n) ? p[i + 2] : 0u;
    return make_uint2(a | (b << 16), c);
}

__global__ void __launch_bounds__(P_NT, 1) k_partition(const __grid_constant__ Params p) {
    extern __shared__ __align__(16) unsigned char smem_raw[];
    uint2* stage = reinterpret_cast<uint2*>(smem_raw);
    int* hist = reinterpret_cast<int*>(smem_raw + (size_t)P_STAGE * 8);
    __shared__ int warp_sums[P_NT / 32];
    static_assert(BINS_PAD == 2 * P_NT, "two bins per thread in the scan");

    const int tid = threadIdx.x;
    const int lane = tid & 31, wid = tid >> 5;
    const unsigned short* ang16 = reinterpret_cast<const unsigned short*>(p.angle);

    if (blockIdx.x == 0 && wid == P_NT / 32 - 1) {
        const int g = lane >> 2, q = lane & 3;
        const unsigned short* wd = reinterpret_cast<const unsigned short*>(p.w_down);
        const unsigned short* wu = reinterpret_cast<const unsigned short*>(p.w_up);
        const unsigned short* ws = reinterpret_cast<const unsigned short*>(p.w_sbf);
        const unsigned short* wr = reinterpret_cast<const unsigned short*>(p.w_rbf);
        uint4 t;
        t.x = (uint32_t)wd[(2 * q) * DE + g] | ((uint32_t)wd[(2 * q + 1) * DE + g] << 16);
        t.y = (uint32_t)wd[(2 * q) * DE + g + 8] | ((uint32_t)wd[(2 * q + 1) * DE + g + 8] << 16);
        t.z = (uint32_t)wd[(2 * q + 8) * DE + g] | ((uint32_t)wd[(2 * q + 9) * DE + g] << 16);
        t.w = (uint32_t)wd[(2 * q + 8) * DE + g + 8] | ((uint32_t)wd[(2 * q + 9) * DE + g + 8] << 16);
        g_frag[lane] = t;
        const int cA = 2 * g, cB = 2 * g + 1;
        t.x = (uint32_t)wu[(2 * q) * DE + cA] | ((uint32_t)wu[(2 * q + 1) * DE + cA] << 16);
        t.y = (uint32_t)wu[(2 * q) * DE + cB] | ((uint32_t)wu[(2 * q + 1) * DE + cB] << 16);
        t.z = (uint32_t)wu[(2 * q + 8) * DE + cA] | ((uint32_t)wu[(2 * q + 9) * DE + cA] << 16);
        t.w = (uint32_t)wu[(2 * q + 8) * DE + cB] | ((uint32_t)wu[(2 * q + 9) * DE + cB] << 16);
        g_frag[32 + lane] = t;
        uint32_t sb[NL][2];
#pragma unroll
        for (int l = 0; l < NL; l++) {
            sb[l][0] = (uint32_t)ws[((2 * q) * NL + l) * DE + g] | ((uint32_t)ws[((2 * q + 1) * NL + l) * DE + g] << 16);
            sb[l][1] = (uint32_t)ws[((2 * q) * NL + l) * DE + g + 8] | ((uint32_t)ws[((2 * q + 1) * NL + l) * DE + g + 8] << 16);
        }
        g_frag[64 + lane] = make_uint4(sb[0][0], sb[0][1], sb[1][0], sb[1][1]);
        t.x = sb[2][0]; t.y = sb[2][1];
        t.z = (uint32_t)wr[(2 * q) * DE + cA] | ((uint32_t)wr[(2 * q + 1) * DE + cA] << 16);
        t.w = (uint32_t)wr[(2 * q) * DE + cB] | ((uint32_t)wr[(2 * q + 1) * DE + cB] << 16);
        g_frag[96 + lane] = t;
    }

    int4 O[P_PER / 4];
    int tile = blockIdx.x;
    if (tile < p.ntiles) {
        const int base = tile * p.tile, n = min(p.tile, p.T - base);
#pragma unroll
        for (int v = 0; v < P_PER / 4; v++) O[v] = ld4_guard(p.idx_out + base, (v * P_NT + tid) * 4, n, -1);
    }
    reinterpret_cast<int2*>(hist)[tid] = make_int2(0, 0);
    if (tid == 0) hist[BINS_PAD] = 0;
    for (; tile < p.ntiles; tile += gridDim.x) {
        const int base = tile * p.tile, n = min(p.tile, p.T - base);
        __syncthreads();
#pragma unroll
        for (int v = 0; v < P_PER / 4; v++) {
            atomicAdd(&hist[min((uint32_t)O[v].x >> NB_LOG, (uint32_t)BINS_PAD)], 1);
            atomicAdd(&hist[min((uint32_t)O[v].y >> NB_LOG, (uint32_t)BINS_PAD)], 1);
            atomicAdd(&hist[min((uint32_t)O[v].z >> NB_LOG, (uint32_t)BINS_PAD)], 1);
            atomicAdd(&hist[min((uint32_t)O[v].w >> NB_LOG, (uint32_t)BINS_PAD)], 1);
        }
        int4 I[P_PER / 4];
        uint2 A[P_PER / 4];
#pragma unroll
        for (int v = 0; v < P_PER / 4; v++) {
            I[v] = ld4_guard(p.idx_in + base, (v * P_NT + tid) * 4, n, 0);
            A[v] = ld4h_guard(ang16 + base, (v * P_NT + tid) * 4, n);
        }
        __syncthreads();
        const int2 c2 = reinterpret_cast<int2*>(hist)[tid];
        const int pc0 = (c2.x + 3) & ~3, pc1 = (c2.y + 3) & ~3;
        int g0 = 0, g1 = 0;
        if (pc0) g0 = atomicAdd(&g_cursor[2 * tid], pc0);
        if (pc1) g1 = atomicAdd(&g_cursor[2 * tid + 1], pc1);
        const int s = pc0 + pc1;
        int inc = s;
#pragma unroll
        for (int o = 1; o < 32; o <<= 1) {
            int t = __shfl_up_sync(0xffffffffu, inc, o);
            if (lane >= o) inc += t;
        }
        if (lane == 31) warp_sums[wid] = inc;
        asm volatile("cp.async.bulk.wait_group.read 0;" ::: "memory");
        __syncthreads();
        int woff;
        {
            int ws = warp_sums[lane];
            int winc = ws;
#pragma unroll
            for (int o = 1; o < 32; o <<= 1) {
                int t = __shfl_up_sync(0xffffffffu, winc, o);
                if (lane >= o) winc += t;
            }
            woff = __shfl_sync(0xffffffffu, winc - ws, wid);
        }
        const int e0 = woff + inc - s, e1 = e0 + pc0;
        reinterpret_cast<int2*>(hist)[tid] = make_int2(e0, e1);
        if (tid == 0) hist[BINS_PAD] = P_STAGE;
        for (int k = c2.x; k < pc0; k++) stage[e0 + k] = make_uint2(0u, 0xffffffffu);
        for (int k = c2.y; k < pc1; k++) stage[e1 + k] = make_uint2(0u, 0xffffffffu);
        __syncthreads();
#pragma unroll
        for (int v = 0; v < P_PER / 4; v++) {
            const uint32_t o[4] = {(uint32_t)O[v].x, (uint32_t)O[v].y, (uint32_t)O[v].z, (uint32_t)O[v].w};
            const uint32_t in[4] = {(uint32_t)I[v].x, (uint32_t)I[v].y, (uint32_t)I[v].z, (uint32_t)I[v].w};
            const uint32_t an[4] = {A[v].x & 0xffffu, A[v].x >> 16, A[v].y & 0xffffu, A[v].y >> 16};
#pragma unroll
            for (int u = 0; u < 4; u++) {
                int pos = atomicAdd(&hist[min(o[u] >> NB_LOG, (uint32_t)BINS_PAD)], 1);
                stage[min(pos, P_STAGE - 1)] = make_uint2((in[u] << 5) | (0x1000000u << (o[u] & 7)), an[u] | ((o[u] & 255u) << 16));
            }
        }
        {
            const int nt = tile + gridDim.x;
            if (nt < p.ntiles) {
                const int nbase = nt * p.tile, nn = min(p.tile, p.T - nbase);
#pragma unroll
                for (int v = 0; v < P_PER / 4; v++) O[v] = ld4_guard(p.idx_out + nbase, (v * P_NT + tid) * 4, nn, -1);
            }
        }
        asm volatile("fence.proxy.async.shared::cta;" ::: "memory");
        __syncthreads();
        if (pc0 && g0 + pc0 <= CAPG)
            asm volatile("cp.async.bulk.global.shared::cta.bulk_group [%0], [%1], %2;"
                         :: "l"(g_records + (size_t)(2 * tid) * CAPG + g0), "r"(smem_u32(stage + e0)), "r"(pc0 * 8) : "memory");
        if (pc1 && g1 + pc1 <= CAPG)
            asm volatile("cp.async.bulk.global.shared::cta.bulk_group [%0], [%1], %2;"
                         :: "l"(g_records + (size_t)(2 * tid + 1) * CAPG + g1), "r"(smem_u32(stage + e1)), "r"(pc1 * 8) : "memory");
        asm volatile("cp.async.bulk.commit_group;" ::: "memory");
        reinterpret_cast<int2*>(hist)[tid] = make_int2(0, 0);
        if (tid == 0) hist[BINS_PAD] = 0;
    }
    asm volatile("cp.async.bulk.wait_group 0;" ::: "memory");
}

constexpr int SM_IDX = 0;
constexpr int SM_C01 = SM_IDX + (CAPS + 16) * 4;
constexpr int SM_C2 = SM_C01 + CAPS * 4;
constexpr int SM_OH = SM_C2 + (CAPS + 16) * 2;
constexpr int SM_RING = SM_OH + CAPS;
constexpr int SM_TOTAL = SM_RING + (G_NT / 32) * G_STAGES * 512;

__device__ __forceinline__ uint32_t lds32(uint32_t a) { uint32_t v; asm volatile("ld.shared.u32 %0, [%1];" : "=r"(v) : "r"(a) : "memory"); return v; }
__device__ __forceinline__ uint2 lds64(uint32_t a) { uint2 v; asm volatile("ld.shared.v2.u32 {%0,%1}, [%2];" : "=r"(v.x), "=r"(v.y) : "r"(a) : "memory"); return v; }
__device__ __forceinline__ uint4 lds128(uint32_t a) { uint4 v; asm volatile("ld.shared.v4.u32 {%0,%1,%2,%3}, [%4];" : "=r"(v.x), "=r"(v.y), "=r"(v.z), "=r"(v.w) : "r"(a) : "memory"); return v; }

__global__ void __launch_bounds__(G_NT, G_BLOCKS) k_gather(const __grid_constant__ Params p) {
    extern __shared__ __align__(128) unsigned char smem_raw[];
    uint32_t* sidx = reinterpret_cast<uint32_t*>(smem_raw + SM_IDX);
    uint4* sc01 = reinterpret_cast<uint4*>(smem_raw + SM_C01);
    unsigned short* sc2 = reinterpret_cast<unsigned short*>(smem_raw + SM_C2);
    uint32_t* soh = reinterpret_cast<uint32_t*>(smem_raw + SM_OH);
    __shared__ int cnts[NB + 32];
    __shared__ int gstart[NGRP + 1];
    __shared__ int warp_sums[NB / 32];

    const int tid = threadIdx.x;
    const int lane = tid & 31, wid = tid >> 5;
    const int bin = blockIdx.x;
    const int total = g_cursor[bin];
    const bool ovf = total > CAPG;
    const int n = ovf ? 0 : total;
    if (ovf) slow_bin(&p, bin);

    const uint4* rec = reinterpret_cast<const uint4*>(g_records + (size_t)bin * CAPG) + tid;
    uint4 r[G_PER / 2];
#pragma unroll
    for (int j = 0; j < G_PER / 2; j++) {
        r[j] = make_uint4(0u, 0xffffffffu, 0u, 0xffffffffu);
        if ((j * G_NT + tid) * 2 < n) r[j] = __ldcs(rec + j * G_NT);
    }
    if (tid < NB) cnts[tid] = 0;
    const unsigned short* fq = reinterpret_cast<const unsigned short*>(p.ang_freq);
    const uint32_t f0 = (uint32_t)fq[0] * 0x10001u, f1 = (uint32_t)fq[1] * 0x10001u, f2 = (uint32_t)fq[2] * 0x10001u;
    const uint32_t fmaxp = max(max(f0 & 0x7fff7fffu, f1 & 0x7fff7fffu), f2 & 0x7fff7fffu);
    const uint32_t dkey = NB + lane;
    __syncthreads();
    if (tid == 0) g_cursor[bin] = 0;
#pragma unroll
    for (int j = 0; j < G_PER / 2; j++) {
        atomicAdd(&cnts[min(r[j].y >> 16, dkey)], 1);
        atomicAdd(&cnts[min(r[j].w >> 16, dkey)], 1);
    }
    __syncthreads();
    int c = 0, inc = 0, cp = 0, npad = 0;
    if (tid < NB) {
        c = cnts[tid];
        int gt = c;
        gt += __shfl_xor_sync(0xffffffffu, gt, 1);
        gt += __shfl_xor_sync(0xffffffffu, gt, 2);
        gt += __shfl_xor_sync(0xffffffffu, gt, 4);
        npad = ((gt + 15) & ~15) - gt;
        cp = c + (((lane & 7) == 7) ? npad : 0);
        inc = cp;
#pragma unroll
        for (int o = 1; o < 32; o <<= 1) {
            int t = __shfl_up_sync(0xffffffffu, inc, o);
            if (lane >= o) inc += t;
        }
        if (lane == 31) warp_sums[wid] = inc;
    }
    __syncthreads();
    if (tid < NB) {
        int woff = 0;
#pragma unroll
        for (int w = 0; w < NB / 32; w++) woff += (w < wid) ? warp_sums[w] : 0;
        const int st = woff + inc - cp;
        cnts[tid] = st;
        if ((lane & 7) == 0) gstart[tid >> 3] = st;
        if (tid == NB - 1) gstart[NGRP] = woff + inc;
        if (tid < 32) cnts[NB + tid] = CAPS;
        const int gend = __shfl_sync(0xffffffffu, woff + inc, lane | 7);
        const int k = lane & 7;
        if (k < npad) { sidx[gend - 1 - k] = 0u; sc2[gend - 1 - k] = 0; }
        if (k + 8 < npad) { sidx[gend - 9 - k] = 0u; sc2[gend - 9 - k] = 0; }
    }
    __syncthreads();
#pragma unroll
    for (int j = 0; j < G_PER / 2; j++) {
        {
            const int pos = min(atomicAdd(&cnts[min(r[j].y >> 16, dkey)], 1), CAPS);
            sidx[pos] = r[j].x;
            sc2[pos] = (unsigned short)r[j].y;
        }
        {
            const int pos = min(atomicAdd(&cnts[min(r[j].w >> 16, dkey)], 1), CAPS);
            sidx[pos] = r[j].z;
            sc2[pos] = (unsigned short)r[j].w;
        }
    }
    __syncthreads();
    {
        const int nch = gstart[NGRP] >> 2;
        for (int i = tid; i < nch; i += G_NT) {
            const uint2 a = reinterpret_cast<const uint2*>(sc2)[i];
            const uint4 w = reinterpret_cast<const uint4*>(sidx)[i];
            soh[i] = prmt(prmt(w.x, w.y, 0x0073), prmt(w.z, w.w, 0x0073), 0x5410);
            uint32_t x0 = mul_bf16x2(a.x, f0), x1 = mul_bf16x2(a.y, f0);
            uint32_t x2 = mul_bf16x2(a.x, f1), x3 = mul_bf16x2(a.y, f1);
            uint32_t x4 = mul_bf16x2(a.x, f2), x5 = mul_bf16x2(a.y, f2);
            uint32_t t = mul_bf16x2(__vmaxu2(a.x & 0x7fff7fffu, a.y & 0x7fff7fffu), fmaxp);
            uint4 o; uint2 o2;
            if ((t >> 16) < 0x4300u && (t & 0xffffu) < 0x4300u) {
                o.x = cos_fast_bf16x2(x0); o.y = cos_fast_bf16x2(x1);
                o.z = cos_fast_bf16x2(x2); o.w = cos_fast_bf16x2(x3);
                o2.x = cos_fast_bf16x2(x4); o2.y = cos_fast_bf16x2(x5);
            } else {
                o.x = cos_slow_bf16x2(x0); o.y = cos_slow_bf16x2(x1);
                o.z = cos_slow_bf16x2(x2); o.w = cos_slow_bf16x2(x3);
                o2.x = cos_slow_bf16x2(x4); o2.y = cos_slow_bf16x2(x5);
            }
            sc01[i] = o;
            reinterpret_cast<uint2*>(sc2)[i] = o2;
        }
    }
    __syncthreads();

    const int g = lane >> 2, q = lane & 3;
    constexpr int GPW = NGRP / (G_NT / 32);
    const int grp0 = wid * GPW;
    const int wbeg = gstart[grp0], wend = gstart[grp0 + GPW];
    const unsigned char* mb = reinterpret_cast<const unsigned char*>(p.m);
    const uint32_t sbase = smem_u32(smem_raw);

    const uint32_t ring = sbase + SM_RING + wid * (G_STAGES * 512);
    const int cj = lane >> 1;
    const int crow = (cj >> 2) * 2 + (cj & 1) + ((cj >> 1) & 1) * 8;
    const uint32_t cdst = ring + (uint32_t)(crow * 32 + (((lane ^ (crow >> 2)) & 1) * 16));
    const unsigned char* msrc = mb + (lane & 1) * 16;
    const int lrow = (lane >> 4) * 8 + (lane & 7);
    const uint32_t lsrc = ring + (uint32_t)(lrow * 32 + ((((lane >> 3) ^ (lrow >> 2)) & 1) * 16));

    uint32_t iaddr = sbase + SM_IDX + (wbeg + cj) * 4;
    const uint32_t iend = sbase + SM_IDX + wend * 4;
    uint32_t ioff = 0;
#pragma unroll
    for (int k = 0; k < G_STAGES - 1; k++) {
        if (iaddr < iend) cp_async_row(cdst + ioff, msrc, lds32(iaddr));
        cp_async_commit();
        iaddr += 64; ioff += 512;
    }
    uint32_t wnext = (iaddr < iend) ? lds32(iaddr) : 0u;

    uint32_t adown[4], aup[4], asbf[NL][2], arb[2];
    {
        const uint4* fr = reinterpret_cast<const uint4*>(g_frag) + lane;
        const uint4 t0 = __ldg(fr), t1 = __ldg(fr + 32), t2 = __ldg(fr + 64), t3 = __ldg(fr + 96);
        adown[0] = t0.x; adown[1] = t0.y; adown[2] = t0.z; adown[3] = t0.w;
        aup[0] = t1.x; aup[1] = t1.y; aup[2] = t1.z; aup[3] = t1.w;
        asbf[0][0] = t2.x; asbf[0][1] = t2.y; asbf[1][0] = t2.z; asbf[1][1] = t2.w;
        asbf[2][0] = t3.x; asbf[2][1] = t3.y; arb[0] = t3.z; arb[1] = t3.w;
    }
    const uint32_t cen = reinterpret_cast<const uint32_t*>(p.centers)[q];

    const int ew = bin * NB + grp0 * 8;
    const unsigned short* pdist = reinterpret_cast<const unsigned short*>(p.dist) + ew + g;
    const uint32_t moff0 = (uint32_t)(ew + 2 * q) * 32u + 4u * g;
    const int nleft = p.E - ew;

    uint32_t a01 = sbase + SM_C01 + ((wbeg >> 2) + q) * 16;
    uint32_t a2 = sbase + SM_C2 + ((wbeg >> 2) + q) * 8;
    uint32_t aoh = sbase + SM_OH + ((wbeg >> 2) + q) * 4;
    uint32_t ohnext = lds32(aoh);
    uint4 c01 = make_uint4(0u, 0u, 0u, 0u);
    uint2 c2 = make_uint2(0u, 0u);
    uint32_t coff = 0;
#pragma unroll 1
    for (int gi = 0; gi < GPW; gi++) {
        const uint32_t aend = sbase + SM_OH + (uint32_t)gstart[grp0 + gi + 1];
        const uint32_t moff = moff0 + gi * 256;
        const bool va = gi * 8 + 2 * q < nleft, vb = gi * 8 + 2 * q + 1 < nleft;
        uint32_t dg = (gi * 8 + g < nleft) ? (uint32_t)pdist[gi * 8] : 0u;
        uint32_t ma = va ? __ldg(reinterpret_cast<const uint32_t*>(mb + moff)) : 0u;
        uint32_t mbv = vb ? __ldg(reinterpret_cast<const uint32_t*>(mb + moff + 32)) : 0u;

        float D[NL][4];
#pragma unroll
        for (int l = 0; l < NL; l++)
#pragma unroll
            for (int c4 = 0; c4 < 4; c4++) D[l][c4] = 0.f;
#pragma unroll 1
        while (aoh < aend) {
            cp_async_row(cdst + ioff, msrc, wnext);
            cp_async_commit();
            iaddr += 64; ioff = (ioff == (G_STAGES - 1) * 512) ? 0 : ioff + 512;
            wnext = (iaddr < iend) ? lds32(iaddr) : 0u;
            const uint32_t kb = ((ohnext >> g) & 0x01010101u) * 0xffu;
            asm volatile("{ .reg .pred p; setp.ne.u32 p, %7, 0;\n\t"
                         "@p ld.shared.v4.u32 {%0,%1,%2,%3}, [%6];\n\t"
                         "@p ld.shared.v2.u32 {%4,%5}, [%8]; }"
                         : "+r"(c01.x), "+r"(c01.y), "+r"(c01.z), "+r"(c01.w), "+r"(c2.x), "+r"(c2.y)
                         : "r"(a01), "r"(kb), "r"(a2) : "memory");
            a01 += 64; a2 += 32; aoh += 16;
            ohnext = lds32(aoh);
            const uint32_t k01 = prmt(kb, 0, 0x1100), k23 = prmt(kb, 0, 0x3322);
            cp_async_wait<G_STAGES - 1>();
            __syncwarp();
            uint32_t a[4];
            ldsm_x4_trans(a, lsrc + coff);
            coff = (coff == (G_STAGES - 1) * 512) ? 0 : coff + 512;
            mma16816(D[0], a, c01.x & k01, c01.y & k23);
            mma16816(D[1], a, c01.z & k01, c01.w & k23);
            mma16816(D[2], a, c2.x & k01, c2.y & k23);
        }
        const uint32_t brbf = rbf_bf16x2(dg * 0x10001u, cen);
        float agg[4] = {0.f, 0.f, 0.f, 0.f};
#pragma unroll
        for (int l = 0; l < NL; l++) {
            const uint32_t h0 = movm(pack_bf16(D[l][0], D[l][1]));
            const uint32_t h1 = movm(pack_bf16(D[l][2], D[l][3]));
            float S[4] = {0.f, 0.f, 0.f, 0.f};
            float G[4] = {0.f, 0.f, 0.f, 0.f};
            mma16816(S, adown, h0, h1);
            mma1688(G, asbf[l], brbf);
#pragma unroll
            for (int c4 = 0; c4 < 4; c4++) agg[c4] = fmaf(S[c4], G[c4], agg[c4]);
        }
        if (ovf) {
            const int ea = ew + gi * 8 + 2 * q;
            if (va) {
                float* pa = g_ovf + (size_t)ea * DE + g;
                agg[0] += __ldcg(pa); agg[2] += __ldcg(pa + 8);
                pa[0] = 0.f; pa[8] = 0.f;
            }
            if (vb) {
                float* pb = g_ovf + (size_t)(ea + 1) * DE + g;
                agg[1] += __ldcg(pb); agg[3] += __ldcg(pb + 8);
                pb[0] = 0.f; pb[8] = 0.f;
            }
        }
        {
            const uint32_t h0 = movm(pack_bf16(agg[0], agg[1]));
            const uint32_t h1 = movm(pack_bf16(agg[2], agg[3]));
            float U[4] = {0.f, 0.f, 0.f, 0.f};
            float R[4] = {0.f, 0.f, 0.f, 0.f};
            mma16816(U, aup, h0, h1);
            mma1688(R, arb, brbf);
            uint32_t oa = pack_bf16(fmaf(U[0], R[0], bf16lo(ma)), fmaf(U[2], R[2], bf16hi(ma)));
            uint32_t ob = pack_bf16(fmaf(U[1], R[1], bf16lo(mbv)), fmaf(U[3], R[3], bf16hi(mbv)));
            unsigned char* ob8 = reinterpret_cast<unsigned char*>(p.out);
            if (va) *reinterpret_cast<uint32_t*>(ob8 + moff) = oa;
            if (vb) *reinterpret_cast<uint32_t*>(ob8 + moff + 32) = ob;
        }
    }
}

}

extern "C" void kernel_launch(void* const* d_in, const int* in_sizes, int n_in,
                              void* d_out, int out_size) {
    Params p;
    p.m = (const __nv_bfloat16*)d_in[0];
    p.idx_in = (const int*)d_in[1];
    p.idx_out = (const int*)d_in[2];
    p.dist = (const __nv_bfloat16*)d_in[3];
    p.angle = (const __nv_bfloat16*)d_in[4];
    p.centers = (const __nv_bfloat16*)d_in[5];
    p.ang_freq = (const __nv_bfloat16*)d_in[6];
    p.w_rbf = (const __nv_bfloat16*)d_in[7];
    p.w_sbf = (const __nv_bfloat16*)d_in[8];
    p.w_down = (const __nv_bfloat16*)d_in[9];
    p.w_up = (const __nv_bfloat16*)d_in[10];
    p.out = (__nv_bfloat16*)d_out;
    p.E = in_sizes[3];
    p.T = in_sizes[1];
    p.nbins = (p.E + NB - 1) / NB;

    const int smem1 = P_STAGE * 8 + (BINS_PAD + 4) * 4;
    const int smem2 = SM_TOTAL;
    static int nsm = 0;
    if (!nsm) {
        cudaFuncSetAttribute(k_partition, cudaFuncAttributeMaxDynamicSharedMemorySize, smem1);
        cudaFuncSetAttribute(k_gather, cudaFuncAttributeMaxDynamicSharedMemorySize, smem2);
        int dev = 0;
        cudaGetDevice(&dev);
        cudaDeviceGetAttribute(&nsm, cudaDevAttrMultiProcessorCount, dev);
    }
    long long per_sm = ((long long)p.T + nsm - 1) / nsm;
    int k = (int)((per_sm + P_TILE_MAX - 1) / P_TILE_MAX);
    if (k < 1) k = 1;
    long long tile = ((long long)p.T + (long long)k * nsm - 1) / ((long long)k * nsm);
    tile = (tile + 15) & ~15LL;
    if (tile > P_TILE_MAX) tile = P_TILE_MAX;
    if (tile < 16) tile = 16;
    p.tile = (int)tile;
    p.ntiles = (int)(((long long)p.T + tile - 1) / tile);
    int g1 = p.ntiles < nsm ? p.ntiles : nsm;
    if (g1 < 1) g1 = 1;
    k_partition<<<g1, P_NT, smem1>>>(p);
    k_gather<<<p.nbins, G_NT, smem2>>>(p);
}
```

```cpp
#include <cuda_runtime.h>
#include <cuda_bf16.h>
#include <stdint.h>

namespace {

constexpr int DE = 16;
constexpr int NR = 8;
constexpr int NL = 3;

constexpr int NB_LOG = 8;
constexpr int NB = 1 << NB_LOG;
constexpr int MAX_E = 400000;
constexpr int MAX_BINS = (MAX_E + NB - 1) / NB;
constexpr int BINS_PAD = 2048;
constexpr int CAPG = 5120;

constexpr int P_NT = 1024;
constexpr int P_PER = 16;
constexpr int P_TILE_MAX = P_NT * P_PER;
constexpr int P_STAGE = P_TILE_MAX + 3 * MAX_BINS + 16;

#define CFG_G_NT 256
#define CFG_G_BLOCKS 3
#define CFG_G_STAGES 3
constexpr int G_NT = CFG_G_NT;
constexpr int G_BLOCKS = CFG_G_BLOCKS;
constexpr int G_PER = CAPG / G_NT;
constexpr int NGRP = NB / 8;
constexpr int CAPS = CAPG + NGRP * 16;
constexpr int G_STAGES = CFG_G_STAGES;

__device__ uint2 g_records[(size_t)MAX_BINS * CAPG];
__device__ int g_cursor[BINS_PAD];
__device__ uint4 g_frag[4 * 32];
__device__ float g_ovf[(size_t)MAX_BINS * NB * DE];

__device__ __forceinline__ float bf16r(float x) { return __bfloat162float(__float2bfloat16_rn(x)); }
__device__ __forceinline__ float bf16lo(uint32_t v) { return __uint_as_float(v << 16); }
__device__ __forceinline__ float bf16hi(uint32_t v) { return __uint_as_float(v & 0xffff0000u); }
__device__ __forceinline__ float ldbf(const __nv_bfloat16* p) { return __bfloat162float(*p); }
__device__ __forceinline__ uint32_t smem_u32(const void* p) { return (uint32_t)__cvta_generic_to_shared(p); }

__device__ __forceinline__ uint32_t pack_bf16(float lo, float hi) {
    __nv_bfloat162 v = __floats2bfloat162_rn(lo, hi);
    return *reinterpret_cast<uint32_t*>(&v);
}
__device__ __forceinline__ uint32_t mul_bf16x2(uint32_t a, uint32_t b) {
    __nv_bfloat162 r = __hmul2(*reinterpret_cast<__nv_bfloat162*>(&a), *reinterpret_cast<__nv_bfloat162*>(&b));
    return *reinterpret_cast<uint32_t*>(&r);
}
__device__ __forceinline__ uint32_t sub_bf16x2(uint32_t a, uint32_t b) {
    __nv_bfloat162 r = __hsub2(*reinterpret_cast<__nv_bfloat162*>(&a), *reinterpret_cast<__nv_bfloat162*>(&b));
    return *reinterpret_cast<uint32_t*>(&r);
}
__device__ __forceinline__ uint32_t cos_fast_bf16x2(uint32_t x) {
    return pack_bf16(__cosf(bf16lo(x)), __cosf(bf16hi(x)));
}
__device__ __noinline__ uint32_t cos_slow_bf16x2(uint32_t x) {
    return pack_bf16(cosf(bf16lo(x)), cosf(bf16hi(x)));
}
__device__ __forceinline__ uint32_t rbf_bf16x2(uint32_t dd, uint32_t cc) {
    uint32_t t = sub_bf16x2(dd, cc);
    t = mul_bf16x2(t, t);
    t = mul_bf16x2(t, 0xC120C120u);
    return pack_bf16(__expf(bf16lo(t)), __expf(bf16hi(t)));
}

__device__ __forceinline__ void mma16816(float* d, const uint32_t* a, uint32_t b0, uint32_t b1) {
    asm volatile("mma.sync.aligned.m16n8k16.row.col.f32.bf16.bf16.f32 {%0,%1,%2,%3}, {%4,%5,%6,%7}, {%8,%9}, {%0,%1,%2,%3};"
                 : "+f"(d[0]), "+f"(d[1]), "+f"(d[2]), "+f"(d[3])
                 : "r"(a[0]), "r"(a[1]), "r"(a[2]), "r"(a[3]), "r"(b0), "r"(b1));
}
__device__ __forceinline__ void mma1688(float* d, const uint32_t* a, uint32_t b) {
    asm volatile("mma.sync.aligned.m16n8k8.row.col.f32.bf16.bf16.f32 {%0,%1,%2,%3}, {%4,%5}, {%6}, {%0,%1,%2,%3};"
                 : "+f"(d[0]), "+f"(d[1]), "+f"(d[2]), "+f"(d[3])
                 : "r"(a[0]), "r"(a[1]), "r"(b));
}
__device__ __forceinline__ uint32_t movm(uint32_t a) {
    uint32_t d;
    asm volatile("movmatrix.sync.aligned.m8n8.trans.b16 %0, %1;" : "=r"(d) : "r"(a));
    return d;
}
__device__ __forceinline__ uint32_t prmt(uint32_t a, uint32_t b, uint32_t sel) {
    uint32_t d;
    asm("prmt.b32 %0, %1, %2, %3;" : "=r"(d) : "r"(a), "r"(b), "r"(sel));
    return d;
}
__device__ __forceinline__ void ldsm_x4_trans(uint32_t* r, uint32_t addr) {
    asm volatile("ldmatrix.sync.aligned.m8n8.x4.trans.shared.b16 {%0,%1,%2,%3}, [%4];"
                 : "=r"(r[0]), "=r"(r[1]), "=r"(r[2]), "=r"(r[3]) : "r"(addr) : "memory");
}
__device__ __forceinline__ void cp_async_row(uint32_t dst, const unsigned char* base, uint32_t w) {
    uint64_t addr;
    asm("mad.wide.u32 %0, %1, 1, %2;" : "=l"(addr) : "r"(w & 0xffffffu), "l"(base));
    asm volatile("{ .reg .pred p; setp.gt.u32 p, %2, 0xffffff; @p cp.async.cg.shared.global [%0], [%1], 16; }" :: "r"(dst), "l"(addr), "r"(w) : "memory");
}
__device__ __forceinline__ void cp_async_commit() { asm volatile("cp.async.commit_group;" ::: "memory"); }
template <int N> __device__ __forceinline__ void cp_async_wait() { asm volatile("cp.async.wait_group %0;" :: "n"(N) : "memory"); }

struct Params {
    const __nv_bfloat16* m;
    const int* idx_in;
    const int* idx_out;
    const __nv_bfloat16* dist;
    const __nv_bfloat16* angle;
    const __nv_bfloat16* centers;
    const __nv_bfloat16* ang_freq;
    const __nv_bfloat16* w_rbf;
    const __nv_bfloat16* w_sbf;
    const __nv_bfloat16* w_down;
    const __nv_bfloat16* w_up;
    __nv_bfloat16* out;
    int E, T, nbins, ntiles, tile;
};

__device__ __noinline__ void slow_bin(const Params* pp, int bin) {
    const Params& p = *pp;
    for (int t = threadIdx.x; t < p.T; t += blockDim.x) {
        const int out = p.idx_out[t];
        if ((out >> NB_LOG) != bin) continue;
        const int in = p.idx_in[t];
        const float ang = ldbf(p.angle + t);
        float mrow[DE], rb[NR], cb[NL];
        for (int k = 0; k < DE; k++) mrow[k] = ldbf(p.m + (size_t)in * DE + k);
        float d = ldbf(p.dist + out);
        for (int r = 0; r < NR; r++) {
            float u = bf16r(d - ldbf(p.centers + r));
            u = bf16r(u * u);
            u = bf16r(-10.0f * u);
            rb[r] = bf16r(__expf(u));
        }
        for (int l = 0; l < NL; l++) cb[l] = bf16r(cosf(bf16r(ldbf(p.ang_freq + l) * ang)));
        for (int c = 0; c < DE; c++) {
            float md = 0.f, s = 0.f;
            for (int k = 0; k < DE; k++) md = fmaf(mrow[k], ldbf(p.w_down + k * DE + c), md);
            for (int r = 0; r < NR; r++)
                for (int l = 0; l < NL; l++) s = fmaf(rb[r] * cb[l], ldbf(p.w_sbf + (r * NL + l) * DE + c), s);
            atomicAdd(&g_ovf[(size_t)out * DE + c], md * s);
        }
    }
    __threadfence();
}

__device__ __forceinline__ int4 ld4_guard(const int* p, int i, int n, int fill) {
    if (i + 3 < n) return __ldcs(reinterpret_cast<const int4*>(p + i));
    int4 r;
    r.x = (i + 0 < n) ? p[i + 0] : fill;
    r.y = (i + 1 < n) ? p[i + 1] : fill;
    r.z = (i + 2 < n) ? p[i + 2] : fill;
    r.w = fill;
    return r;
}
__device__ __forceinline__ uint2 ld4h_guard(const unsigned short* p, int i, int n) {
    if (i + 3 < n) return __ldcs(reinterpret_cast<const uint2*>(p + i));
    uint32_t a = (i + 0 < n) ? p[i + 0] : 0u, b = (i + 1 < n) ? p[i + 1] : 0u, c = (i + 2 < n) ? p[i + 2] : 0u;
    return make_uint2(a | (b << 16), c);
}

__global__ void __launch_bounds__(P_NT, 1) k_partition(const __grid_constant__ Params p) {
    extern __shared__ __align__(16) unsigned char smem_raw[];
    uint2* stage = reinterpret_cast<uint2*>(smem_raw);
    int* hist = reinterpret_cast<int*>(smem_raw + (size_t)P_STAGE * 8);
    __shared__ int warp_sums[P_NT / 32];
    static_assert(BINS_PAD == 2 * P_NT, "two bins per thread in the scan");

    const int tid = threadIdx.x;
    const int lane = tid & 31, wid = tid >> 5;
    const unsigned short* ang16 = reinterpret_cast<const unsigned short*>(p.angle);

    if (blockIdx.x == 0 && wid == P_NT / 32 - 1) {
        const int g = lane >> 2, q = lane & 3;
        const unsigned short* wd = reinterpret_cast<const unsigned short*>(p.w_down);
        const unsigned short* wu = reinterpret_cast<const unsigned short*>(p.w_up);
        const unsigned short* ws = reinterpret_cast<const unsigned short*>(p.w_sbf);
        const unsigned short* wr = reinterpret_cast<const unsigned short*>(p.w_rbf);
        uint4 t;
        t.x = (uint32_t)wd[(2 * q) * DE + g] | ((uint32_t)wd[(2 * q + 1) * DE + g] << 16);
        t.y = (uint32_t)wd[(2 * q) * DE + g + 8] | ((uint32_t)wd[(2 * q + 1) * DE + g + 8] << 16);
        t.z = (uint32_t)wd[(2 * q + 8) * DE + g] | ((uint32_t)wd[(2 * q + 9) * DE + g] << 16);
        t.w = (uint32_t)wd[(2 * q + 8) * DE + g + 8] | ((uint32_t)wd[(2 * q + 9) * DE + g + 8] << 16);
        g_frag[lane] = t;
        const int cA = 2 * g, cB = 2 * g + 1;
        t.x = (uint32_t)wu[(2 * q) * DE + cA] | ((uint32_t)wu[(2 * q + 1) * DE + cA] << 16);
        t.y = (uint32_t)wu[(2 * q) * DE + cB] | ((uint32_t)wu[(2 * q + 1) * DE + cB] << 16);
        t.z = (uint32_t)wu[(2 * q + 8) * DE + cA] | ((uint32_t)wu[(2 * q + 9) * DE + cA] << 16);
        t.w = (uint32_t)wu[(2 * q + 8) * DE + cB] | ((uint32_t)wu[(2 * q + 9) * DE + cB] << 16);
        g_frag[32 + lane] = t;
        uint32_t sb[NL][2];
#pragma unroll
        for (int l = 0; l < NL; l++) {
            sb[l][0] = (uint32_t)ws[((2 * q) * NL + l) * DE + g] | ((uint32_t)ws[((2 * q + 1) * NL + l) * DE + g] << 16);
            sb[l][1] = (uint32_t)ws[((2 * q) * NL + l) * DE + g + 8] | ((uint32_t)ws[((2 * q + 1) * NL + l) * DE + g + 8] << 16);
        }
        g_frag[64 + lane] = make_uint4(sb[0][0], sb[0][1], sb[1][0], sb[1][1]);
        t.x = sb[2][0]; t.y = sb[2][1];
        t.z = (uint32_t)wr[(2 * q) * DE + cA] | ((uint32_t)wr[(2 * q + 1) * DE + cA] << 16);
        t.w = (uint32_t)wr[(2 * q) * DE + cB] | ((uint32_t)wr[(2 * q + 1) * DE + cB] << 16);
        g_frag[96 + lane] = t;
    }

    int4 O[P_PER / 4];
    int tile = blockIdx.x;
    if (tile < p.ntiles) {
        const int base = tile * p.tile, n = min(p.tile, p.T - base);
#pragma unroll
        for (int v = 0; v < P_PER / 4; v++) O[v] = ld4_guard(p.idx_out + base, (v * P_NT + tid) * 4, n, -1);
    }
    reinterpret_cast<int2*>(hist)[tid] = make_int2(0, 0);
    if (tid == 0) hist[BINS_PAD] = 0;
    for (; tile < p.ntiles; tile += gridDim.x) {
        const int base = tile * p.tile, n = min(p.tile, p.T - base);
        __syncthreads();
#pragma unroll
        for (int v = 0; v < P_PER / 4; v++) {
            atomicAdd(&hist[min((uint32_t)O[v].x >> NB_LOG, (uint32_t)BINS_PAD)], 1);
            atomicAdd(&hist[min((uint32_t)O[v].y >> NB_LOG, (uint32_t)BINS_PAD)], 1);
            atomicAdd(&hist[min((uint32_t)O[v].z >> NB_LOG, (uint32_t)BINS_PAD)], 1);
            atomicAdd(&hist[min((uint32_t)O[v].w >> NB_LOG, (uint32_t)BINS_PAD)], 1);
        }
        int4 I[P_PER / 4];
        uint2 A[P_PER / 4];
#pragma unroll
        for (int v = 0; v < P_PER / 4; v++) {
            I[v] = ld4_guard(p.idx_in + base, (v * P_NT + tid) * 4, n, 0);
            A[v] = ld4h_guard(ang16 + base, (v * P_NT + tid) * 4, n);
        }
        __syncthreads();
        const int2 c2 = reinterpret_cast<int2*>(hist)[tid];
        const int pc0 = (c2.x + 3) & ~3, pc1 = (c2.y + 3) & ~3;
        int g0 = 0, g1 = 0;
        if (pc0) g0 = atomicAdd(&g_cursor[2 * tid], pc0);
        if (pc1) g1 = atomicAdd(&g_cursor[2 * tid + 1], pc1);
        const int s = pc0 + pc1;
        int inc = s;
#pragma unroll
        for (int o = 1; o < 32; o <<= 1) {
            int t = __shfl_up_sync(0xffffffffu, inc, o);
            if (lane >= o) inc += t;
        }
        if (lane == 31) warp_sums[wid] = inc;
        asm volatile("cp.async.bulk.wait_group.read 0;" ::: "memory");
        __syncthreads();
        int woff;
        {
            int ws = warp_sums[lane];
            int winc = ws;
#pragma unroll
            for (int o = 1; o < 32; o <<= 1) {
                int t = __shfl_up_sync(0xffffffffu, winc, o);
                if (lane >= o) winc += t;
            }
            woff = __shfl_sync(0xffffffffu, winc - ws, wid);
        }
        const int e0 = woff + inc - s, e1 = e0 + pc0;
        reinterpret_cast<int2*>(hist)[tid] = make_int2(e0, e1);
        if (tid == 0) hist[BINS_PAD] = P_STAGE;
        for (int k = c2.x; k < pc0; k++) stage[e0 + k] = make_uint2(0u, 0xffffffffu);
        for (int k = c2.y; k < pc1; k++) stage[e1 + k] = make_uint2(0u, 0xffffffffu);
        __syncthreads();
#pragma unroll
        for (int v = 0; v < P_PER / 4; v++) {
            const uint32_t o[4] = {(uint32_t)O[v].x, (uint32_t)O[v].y, (uint32_t)O[v].z, (uint32_t)O[v].w};
            const uint32_t in[4] = {(uint32_t)I[v].x, (uint32_t)I[v].y, (uint32_t)I[v].z, (uint32_t)I[v].w};
            const uint32_t an[4] = {A[v].x & 0xffffu, A[v].x >> 16, A[v].y & 0xffffu, A[v].y >> 16};
#pragma unroll
            for (int u = 0; u < 4; u++) {
                int pos = atomicAdd(&hist[min(o[u] >> NB_LOG, (uint32_t)BINS_PAD)], 1);
                stage[min(pos, P_STAGE - 1)] = make_uint2((in[u] << 5) | (0x1000000u << (o[u] & 7)), an[u] | ((o[u] & 255u) << 16));
            }
        }
        {
            const int nt = tile + gridDim.x;
            if (nt < p.ntiles) {
                const int nbase = nt * p.tile, nn = min(p.tile, p.T - nbase);
#pragma unroll
                for (int v = 0; v < P_PER / 4; v++) O[v] = ld4_guard(p.idx_out + nbase, (v * P_NT + tid) * 4, nn, -1);
            }
        }
        asm volatile("fence.proxy.async.shared::cta;" ::: "memory");
        __syncthreads();
        if (pc0 && g0 + pc0 <= CAPG)
            asm volatile("cp.async.bulk.global.shared::cta.bulk_group [%0], [%1], %2;"
                         :: "l"(g_records + (size_t)(2 * tid) * CAPG + g0), "r"(smem_u32(stage + e0)), "r"(pc0 * 8) : "memory");
        if (pc1 && g1 + pc1 <= CAPG)
            asm volatile("cp.async.bulk.global.shared::cta.bulk_group [%0], [%1], %2;"
                         :: "l"(g_records + (size_t)(2 * tid + 1) * CAPG + g1), "r"(smem_u32(stage + e1)), "r"(pc1 * 8) : "memory");
        asm volatile("cp.async.bulk.commit_group;" ::: "memory");
        reinterpret_cast<int2*>(hist)[tid] = make_int2(0, 0);
        if (tid == 0) hist[BINS_PAD] = 0;
    }
    asm volatile("cp.async.bulk.wait_group 0;" ::: "memory");
}

constexpr int SM_IDX = 0;
constexpr int SM_C01 = SM_IDX + (CAPS + 16) * 4;
constexpr int SM_C2 = SM_C01 + CAPS * 4;
constexpr int SM_OH = SM_C2 + (CAPS + 16) * 2;
constexpr int SM_RING = SM_OH + CAPS;
constexpr int SM_TOTAL = SM_RING + (G_NT / 32) * G_STAGES * 512;

__device__ __forceinline__ uint32_t lds32(uint32_t a) { uint32_t v; asm volatile("ld.shared.u32 %0, [%1];" : "=r"(v) : "r"(a) : "memory"); return v; }
__device__ __forceinline__ uint2 lds64(uint32_t a) { uint2 v; asm volatile("ld.shared.v2.u32 {%0,%1}, [%2];" : "=r"(v.x), "=r"(v.y) : "r"(a) : "memory"); return v; }
__device__ __forceinline__ uint4 lds128(uint32_t a) { uint4 v; asm volatile("ld.shared.v4.u32 {%0,%1,%2,%3}, [%4];" : "=r"(v.x), "=r"(v.y), "=r"(v.z), "=r"(v.w) : "r"(a) : "memory"); return v; }

__global__ void __launch_bounds__(G_NT, G_BLOCKS) k_gather(const __grid_constant__ Params p) {
    extern __shared__ __align__(128) unsigned char smem_raw[];
    uint32_t* sidx = reinterpret_cast<uint32_t*>(smem_raw + SM_IDX);
    uint4* sc01 = reinterpret_cast<uint4*>(smem_raw + SM_C01);
    unsigned short* sc2 = reinterpret_cast<unsigned short*>(smem_raw + SM_C2);
    uint32_t* soh = reinterpret_cast<uint32_t*>(smem_raw + SM_OH);
    __shared__ int cnts[NB + 32];
    __shared__ int gstart[NGRP + 1];
    __shared__ int warp_sums[NB / 32];

    const int tid = threadIdx.x;
    const int lane = tid & 31, wid = tid >> 5;
    const int bin = blockIdx.x;
    const int total = g_cursor[bin];
    const bool ovf = total > CAPG;
    const int n = ovf ? 0 : total;
    if (ovf) slow_bin(&p, bin);

    const uint4* rec = reinterpret_cast<const uint4*>(g_records + (size_t)bin * CAPG) + tid;
    uint4 r[G_PER / 2];
#pragma unroll
    for (int j = 0; j < G_PER / 2; j++) {
        r[j] = make_uint4(0u, 0xffffffffu, 0u, 0xffffffffu);
        if ((j * G_NT + tid) * 2 < n) r[j] = __ldcs(rec + j * G_NT);
    }
    if (tid < NB) cnts[tid] = 0;
    for (int i = tid; i < (G_NT / 32) * G_STAGES * 32; i += G_NT)
        reinterpret_cast<uint4*>(smem_raw + SM_RING)[i] = make_uint4(0u, 0u, 0u, 0u);
    const unsigned short* fq = reinterpret_cast<const unsigned short*>(p.ang_freq);
    const uint32_t f0 = (uint32_t)fq[0] * 0x10001u, f1 = (uint32_t)fq[1] * 0x10001u, f2 = (uint32_t)fq[2] * 0x10001u;
    const uint32_t fmaxp = max(max(f0 & 0x7fff7fffu, f1 & 0x7fff7fffu), f2 & 0x7fff7fffu);
    const uint32_t dkey = NB + lane;
    __syncthreads();
    if (tid == 0) g_cursor[bin] = 0;
#pragma unroll
    for (int j = 0; j < G_PER / 2; j++) {
        atomicAdd(&cnts[min(r[j].y >> 16, dkey)], 1);
        atomicAdd(&cnts[min(r[j].w >> 16, dkey)], 1);
    }
    __syncthreads();
    int c = 0, inc = 0, cp = 0, npad = 0;
    if (tid < NB) {
        c = cnts[tid];
        int gt = c;
        gt += __shfl_xor_sync(0xffffffffu, gt, 1);
        gt += __shfl_xor_sync(0xffffffffu, gt, 2);
        gt += __shfl_xor_sync(0xffffffffu, gt, 4);
        npad = ((gt + 15) & ~15) - gt;
        cp = c + (((lane & 7) == 7) ? npad : 0);
        inc = cp;
#pragma unroll
        for (int o = 1; o < 32; o <<= 1) {
            int t = __shfl_up_sync(0xffffffffu, inc, o);
            if (lane >= o) inc += t;
        }
        if (lane == 31) warp_sums[wid] = inc;
    }
    __syncthreads();
    if (tid < NB) {
        int woff = 0;
#pragma unroll
        for (int w = 0; w < NB / 32; w++) woff += (w < wid) ? warp_sums[w] : 0;
        const int st = woff + inc - cp;
        cnts[tid] = st;
        if ((lane & 7) == 0) gstart[tid >> 3] = st;
        if (tid == NB - 1) gstart[NGRP] = woff + inc;
        if (tid < 32) cnts[NB + tid] = CAPS;
        const int gend = __shfl_sync(0xffffffffu, woff + inc, lane | 7);
        const int k = lane & 7;
        if (k < npad) { sidx[gend - 1 - k] = 0u; sc2[gend - 1 - k] = 0; }
        if (k + 8 < npad) { sidx[gend - 9 - k] = 0u; sc2[gend - 9 - k] = 0; }
    }
    __syncthreads();
#pragma unroll
    for (int j = 0; j < G_PER / 2; j++) {
        {
            const int pos = min(atomicAdd(&cnts[min(r[j].y >> 16, dkey)], 1), CAPS);
            sidx[pos] = r[j].x;
            sc2[pos] = (unsigned short)r[j].y;
        }
        {
            const int pos = min(atomicAdd(&cnts[min(r[j].w >> 16, dkey)], 1), CAPS);
            sidx[pos] = r[j].z;
            sc2[pos] = (unsigned short)r[j].w;
        }
    }
    __syncthreads();
    {
        const int nch = gstart[NGRP] >> 2;
        for (int i = tid; i < nch; i += G_NT) {
            const uint2 a = reinterpret_cast<const uint2*>(sc2)[i];
            const uint4 w = reinterpret_cast<const uint4*>(sidx)[i];
            soh[i] = prmt(prmt(w.x, w.y, 0x0073), prmt(w.z, w.w, 0x0073), 0x5410);
            uint32_t x0 = mul_bf16x2(a.x, f0), x1 = mul_bf16x2(a.y, f0);
            uint32_t x2 = mul_bf16x2(a.x, f1), x3 = mul_bf16x2(a.y, f1);
            uint32_t x4 = mul_bf16x2(a.x, f2), x5 = mul_bf16x2(a.y, f2);
            uint32_t t = mul_bf16x2(__vmaxu2(a.x & 0x7fff7fffu, a.y & 0x7fff7fffu), fmaxp);
            uint4 o; uint2 o2;
            if ((t >> 16) < 0x4300u && (t & 0xffffu) < 0x4300u) {
                o.x = cos_fast_bf16x2(x0); o.y = cos_fast_bf16x2(x1);
                o.z = cos_fast_bf16x2(x2); o.w = cos_fast_bf16x2(x3);
                o2.x = cos_fast_bf16x2(x4); o2.y = cos_fast_bf16x2(x5);
            } else {
                o.x = cos_slow_bf16x2(x0); o.y = cos_slow_bf16x2(x1);
                o.z = cos_slow_bf16x2(x2); o.w = cos_slow_bf16x2(x3);
                o2.x = cos_slow_bf16x2(x4); o2.y = cos_slow_bf16x2(x5);
            }
            sc01[i] = o;
            reinterpret_cast<uint2*>(sc2)[i] = o2;
        }
    }
    __syncthreads();

    const int g = lane >> 2, q = lane & 3;
    constexpr int GPW = NGRP / (G_NT / 32);
    const int grp0 = wid * GPW;
    const int wbeg = gstart[grp0], wend = gstart[grp0 + GPW];
    const unsigned char* mb = reinterpret_cast<const unsigned char*>(p.m);
    const uint32_t sbase = smem_u32(smem_raw);

    const uint32_t ring = sbase + SM_RING + wid * (G_STAGES * 512);
    const int cj = lane >> 1;
    const int crow = (cj >> 2) * 2 + (cj & 1) + ((cj >> 1) & 1) * 8;
    const uint32_t cdst = ring + (uint32_t)(crow * 32 + (((lane ^ (crow >> 2)) & 1) * 16));
    const unsigned char* msrc = mb + (lane & 1) * 16;
    const int lrow = (lane >> 4) * 8 + (lane & 7);
    const uint32_t lsrc = ring + (uint32_t)(lrow * 32 + ((((lane >> 3) ^ (lrow >> 2)) & 1) * 16));

    uint32_t iaddr = sbase + SM_IDX + (wbeg + cj) * 4;
    const uint32_t iend = sbase + SM_IDX + wend * 4;
    uint32_t ioff = 0;
#pragma unroll
    for (int k = 0; k < G_STAGES - 1; k++) {
        if (iaddr < iend) cp_async_row(cdst + ioff, msrc, lds32(iaddr));
        cp_async_commit();
        iaddr += 64; ioff += 512;
    }
    uint32_t wnext = (iaddr < iend) ? lds32(iaddr) : 0u;

    uint32_t adown[4], aup[4], asbf[NL][2], arb[2];
    {
        const uint4* fr = reinterpret_cast<const uint4*>(g_frag) + lane;
        const uint4 t0 = __ldg(fr), t1 = __ldg(fr + 32), t2 = __ldg(fr + 64), t3 = __ldg(fr + 96);
        adown[0] = t0.x; adown[1] = t0.y; adown[2] = t0.z; adown[3] = t0.w;
        aup[0] = t1.x; aup[1] = t1.y; aup[2] = t1.z; aup[3] = t1.w;
        asbf[0][0] = t2.x; asbf[0][1] = t2.y; asbf[1][0] = t2.z; asbf[1][1] = t2.w;
        asbf[2][0] = t3.x; asbf[2][1] = t3.y; arb[0] = t3.z; arb[1] = t3.w;
    }
    const uint32_t cen = reinterpret_cast<const uint32_t*>(p.centers)[q];

    const int ew = bin * NB + grp0 * 8;
    const unsigned short* pdist = reinterpret_cast<const unsigned short*>(p.dist) + ew + g;
    const uint32_t moff0 = (uint32_t)(ew + 2 * q) * 32u + 4u * g;
    const int nleft = p.E - ew;

    uint32_t a01 = sbase + SM_C01 + ((wbeg >> 2) + q) * 16;
    uint32_t a2 = sbase + SM_C2 + ((wbeg >> 2) + q) * 8;
    uint32_t aoh = sbase + SM_OH + ((wbeg >> 2) + q) * 4;
    uint32_t ohnext = lds32(aoh);
    uint4 c01 = make_uint4(0u, 0u, 0u, 0u);
    uint2 c2 = make_uint2(0u, 0u);
#pragma unroll 1
    for (int gi = 0; gi < GPW; gi++) {
        const uint32_t aend = sbase + SM_OH + (uint32_t)gstart[grp0 + gi + 1];
        const uint32_t moff = moff0 + gi * 256;
        const bool va = gi * 8 + 2 * q < nleft, vb = gi * 8 + 2 * q + 1 < nleft;
        uint32_t dg = (gi * 8 + g < nleft) ? (uint32_t)pdist[gi * 8] : 0u;
        uint32_t ma = va ? __ldg(reinterpret_cast<const uint32_t*>(mb + moff)) : 0u;
        uint32_t mbv = vb ? __ldg(reinterpret_cast<const uint32_t*>(mb + moff + 32)) : 0u;

        float D[NL][4];
#pragma unroll
        for (int l = 0; l < NL; l++)
#pragma unroll
            for (int c4 = 0; c4 < 4; c4++) D[l][c4] = 0.f;
#pragma unroll 1
        while (aoh < aend) {
            cp_async_row(cdst + ioff, msrc, wnext);
            cp_async_commit();
            iaddr += 64; ioff = (ioff == (G_STAGES - 1) * 512) ? 0 : ioff + 512;
            wnext = (iaddr < iend) ? lds32(iaddr) : 0u;
            const uint32_t kb = (ohnext >> g) & 0x01010101u;
            asm volatile("{ .reg .pred p; setp.ne.u32 p, %7, 0;\n\t"
                         "@p ld.shared.v4.u32 {%0,%1,%2,%3}, [%6];\n\t"
                         "@p ld.shared.v2.u32 {%4,%5}, [%8]; }"
                         : "+r"(c01.x), "+r"(c01.y), "+r"(c01.z), "+r"(c01.w), "+r"(c2.x), "+r"(c2.y)
                         : "r"(a01), "r"(kb), "r"(a2) : "memory");
            a01 += 64; a2 += 32; aoh += 16;
            ohnext = lds32(aoh);
            const uint32_t k01 = prmt(kb, 0, 0x4140) * 0x3F80u, k23 = prmt(kb, 0, 0x4342) * 0x3F80u;
            cp_async_wait<G_STAGES - 1>();
            __syncwarp();
            uint32_t a[4];
            ldsm_x4_trans(a, lsrc + ioff);
            mma16816(D[0], a, mul_bf16x2(c01.x, k01), mul_bf16x2(c01.y, k23));
            mma16816(D[1], a, mul_bf16x2(c01.z, k01), mul_bf16x2(c01.w, k23));
            mma16816(D[2], a, mul_bf16x2(c2.x, k01), mul_bf16x2(c2.y, k23));
        }
        const uint32_t brbf = rbf_bf16x2(dg * 0x10001u, cen);
        float agg[4] = {0.f, 0.f, 0.f, 0.f};
#pragma unroll
        for (int l = 0; l < NL; l++) {
            const uint32_t h0 = movm(pack_bf16(D[l][0], D[l][1]));
            const uint32_t h1 = movm(pack_bf16(D[l][2], D[l][3]));
            float S[4] = {0.f, 0.f, 0.f, 0.f};
            float G[4] = {0.f, 0.f, 0.f, 0.f};
            mma16816(S, adown, h0, h1);
            mma1688(G, asbf[l], brbf);
#pragma unroll
            for (int c4 = 0; c4 < 4; c4++) agg[c4] = fmaf(S[c4], G[c4], agg[c4]);
        }
        if (ovf) {
            const int ea = ew + gi * 8 + 2 * q;
            if (va) {
                float* pa = g_ovf + (size_t)ea * DE + g;
                agg[0] += __ldcg(pa); agg[2] += __ldcg(pa + 8);
                pa[0] = 0.f; pa[8] = 0.f;
            }
            if (vb) {
                float* pb = g_ovf + (size_t)(ea + 1) * DE + g;
                agg[1] += __ldcg(pb); agg[3] += __ldcg(pb + 8);
                pb[0] = 0.f; pb[8] = 0.f;
            }
        }
        {
            const uint32_t h0 = movm(pack_bf16(agg[0], agg[1]));
            const uint32_t h1 = movm(pack_bf16(agg[2], agg[3]));
            float U[4] = {0.f, 0.f, 0.f, 0.f};
            float R[4] = {0.f, 0.f, 0.f, 0.f};
            mma16816(U, aup, h0, h1);
            mma1688(R, arb, brbf);
            uint32_t oa = pack_bf16(fmaf(U[0], R[0], bf16lo(ma)), fmaf(U[2], R[2], bf16hi(ma)));
            uint32_t ob = pack_bf16(fmaf(U[1], R[1], bf16lo(mbv)), fmaf(U[3], R[3], bf16hi(mbv)));
            unsigned char* ob8 = reinterpret_cast<unsigned char*>(p.out);
            if (va) *reinterpret_cast<uint32_t*>(ob8 + moff) = oa;
            if (vb) *reinterpret_cast<uint32_t*>(ob8 + moff + 32) = ob;
        }
    }
}

}

extern "C" void kernel_launch(void* const* d_in, const int* in_sizes, int n_in,
                              void* d_out, int out_size) {
    Params p;
    p.m = (const __nv_bfloat16*)d_in[0];
    p.idx_in = (const int*)d_in[1];
    p.idx_out = (const int*)d_in[2];
    p.dist = (const __nv_bfloat16*)d_in[3];
    p.angle = (const __nv_bfloat16*)d_in[4];
    p.centers = (const __nv_bfloat16*)d_in[5];
    p.ang_freq = (const __nv_bfloat16*)d_in[6];
    p.w_rbf = (const __nv_bfloat16*)d_in[7];
    p.w_sbf = (const __nv_bfloat16*)d_in[8];
    p.w_down = (const __nv_bfloat16*)d_in[9];
    p.w_up = (const __nv_bfloat16*)d_in[10];
    p.out = (__nv_bfloat16*)d_out;
    p.E = in_sizes[3];
    p.T = in_sizes[1];
    p.nbins = (p.E + NB - 1) / NB;

    const int smem1 = P_STAGE * 8 + (BINS_PAD + 4) * 4;
    const int smem2 = SM_TOTAL;
    static int nsm = 0;
    if (!nsm) {
        cudaFuncSetAttribute(k_partition, cudaFuncAttributeMaxDynamicSharedMemorySize, smem1);
        cudaFuncSetAttribute(k_gather, cudaFuncAttributeMaxDynamicSharedMemorySize, smem2);
        int dev = 0;
        cudaGetDevice(&dev);
        cudaDeviceGetAttribute(&nsm, cudaDevAttrMultiProcessorCount, dev);
    }
    long long per_sm = ((long long)p.T + nsm - 1) / nsm;
    int k = (int)((per_sm + P_TILE_MAX - 1) / P_TILE_MAX);
    if (k < 1) k = 1;
    long long tile = ((long long)p.T + (long long)k * nsm - 1) / ((long long)k * nsm);
    tile = (tile + 15) & ~15LL;
    if (tile > P_TILE_MAX) tile = P_TILE_MAX;
    if (tile < 16) tile = 16;
    p.tile = (int)tile;
    p.ntiles = (int)(((long long)p.T + tile - 1) / tile);
    int g1 = p.ntiles < nsm ? p.ntiles : nsm;
    if (g1 < 1) g1 = 1;
    k_partition<<<g1, P_NT, smem1>>>(p);
    k_gather<<<p.nbins, G_NT, smem2>>>(p);
}
```

```cpp
#include <cuda_runtime.h>
#include <cuda_bf16.h>
#include <stdint.h>

namespace {

constexpr int DE = 16;
constexpr int NR = 8;
constexpr int NL = 3;

constexpr int NB_LOG = 8;
constexpr int NB = 1 << NB_LOG;
constexpr int MAX_E = 400000;
constexpr int MAX_BINS = (MAX_E + NB - 1) / NB;
constexpr int BINS_PAD = 2048;
constexpr int CAPG = 5120;

constexpr int P_NT = 1024;
constexpr int P_PER = 16;
constexpr int P_TILE_MAX = P_NT * P_PER;
constexpr int P_STAGE = P_TILE_MAX + 3 * MAX_BINS + 16;

#define CFG_G_NT 256
#define CFG_G_BLOCKS 3
#define CFG_G_STAGES 2
constexpr int G_NT = CFG_G_NT;
constexpr int G_BLOCKS = CFG_G_BLOCKS;
constexpr int G_PER = CAPG / G_NT;
constexpr int NGRP = NB / 8;
constexpr int CAPS = 5120;
constexpr int G_STAGES = CFG_G_STAGES;

__device__ uint2 g_records[(size_t)MAX_BINS * CAPG];
__device__ int g_cursor[BINS_PAD];
__device__ uint4 g_frag[4 * 32];
__device__ float g_ovf[(size_t)MAX_BINS * NB * DE];

__device__ __forceinline__ float bf16r(float x) { return __bfloat162float(__float2bfloat16_rn(x)); }
__device__ __forceinline__ float bf16lo(uint32_t v) { return __uint_as_float(v << 16); }
__device__ __forceinline__ float bf16hi(uint32_t v) { return __uint_as_float(v & 0xffff0000u); }
__device__ __forceinline__ float ldbf(const __nv_bfloat16* p) { return __bfloat162float(*p); }
__device__ __forceinline__ uint32_t smem_u32(const void* p) { return (uint32_t)__cvta_generic_to_shared(p); }

__device__ __forceinline__ uint32_t pack_bf16(float lo, float hi) {
    __nv_bfloat162 v = __floats2bfloat162_rn(lo, hi);
    return *reinterpret_cast<uint32_t*>(&v);
}
__device__ __forceinline__ uint32_t mul_bf16x2(uint32_t a, uint32_t b) {
    __nv_bfloat162 r = __hmul2(*reinterpret_cast<__nv_bfloat162*>(&a), *reinterpret_cast<__nv_bfloat162*>(&b));
    return *reinterpret_cast<uint32_t*>(&r);
}
__device__ __forceinline__ uint32_t sub_bf16x2(uint32_t a, uint32_t b) {
    __nv_bfloat162 r = __hsub2(*reinterpret_cast<__nv_bfloat162*>(&a), *reinterpret_cast<__nv_bfloat162*>(&b));
    return *reinterpret_cast<uint32_t*>(&r);
}
__device__ __forceinline__ uint32_t cos_fast_bf16x2(uint32_t x) {
    return pack_bf16(__cosf(bf16lo(x)), __cosf(bf16hi(x)));
}
__device__ __noinline__ uint32_t cos_slow_bf16x2(uint32_t x) {
    return pack_bf16(cosf(bf16lo(x)), cosf(bf16hi(x)));
}
__device__ __forceinline__ uint32_t rbf_bf16x2(uint32_t dd, uint32_t cc) {
    uint32_t t = sub_bf16x2(dd, cc);
    t = mul_bf16x2(t, t);
    t = mul_bf16x2(t, 0xC120C120u);
    return pack_bf16(__expf(bf16lo(t)), __expf(bf16hi(t)));
}

__device__ __forceinline__ void mma16816(float* d, const uint32_t* a, uint32_t b0, uint32_t b1) {
    asm volatile("mma.sync.aligned.m16n8k16.row.col.f32.bf16.bf16.f32 {%0,%1,%2,%3}, {%4,%5,%6,%7}, {%8,%9}, {%0,%1,%2,%3};"
                 : "+f"(d[0]), "+f"(d[1]), "+f"(d[2]), "+f"(d[3])
                 : "r"(a[0]), "r"(a[1]), "r"(a[2]), "r"(a[3]), "r"(b0), "r"(b1));
}
__device__ __forceinline__ void mma1688(float* d, const uint32_t* a, uint32_t b) {
    asm volatile("mma.sync.aligned.m16n8k8.row.col.f32.bf16.bf16.f32 {%0,%1,%2,%3}, {%4,%5}, {%6}, {%0,%1,%2,%3};"
                 : "+f"(d[0]), "+f"(d[1]), "+f"(d[2]), "+f"(d[3])
                 : "r"(a[0]), "r"(a[1]), "r"(b));
}
__device__ __forceinline__ uint32_t movm(uint32_t a) {
    uint32_t d;
    asm volatile("movmatrix.sync.aligned.m8n8.trans.b16 %0, %1;" : "=r"(d) : "r"(a));
    return d;
}
__device__ __forceinline__ uint32_t prmt(uint32_t a, uint32_t b, uint32_t sel) {
    uint32_t d;
    asm("prmt.b32 %0, %1, %2, %3;" : "=r"(d) : "r"(a), "r"(b), "r"(sel));
    return d;
}
__device__ __forceinline__ void ldsm_x4_trans(uint32_t* r, uint32_t addr) {
    asm volatile("ldmatrix.sync.aligned.m8n8.x4.trans.shared.b16 {%0,%1,%2,%3}, [%4];"
                 : "=r"(r[0]), "=r"(r[1]), "=r"(r[2]), "=r"(r[3]) : "r"(addr) : "memory");
}
__device__ __forceinline__ void cp_async_row(uint32_t dst, const unsigned char* base, uint32_t w) {
    uint64_t addr;
    asm("mad.wide.u32 %0, %1, 1, %2;" : "=l"(addr) : "r"(w & 0xffffffu), "l"(base));
    asm volatile("{ .reg .pred p; setp.gt.u32 p, %2, 0xffffff; @p cp.async.cg.shared.global [%0], [%1], 16; }" :: "r"(dst), "l"(addr), "r"(w) : "memory");
}
__device__ __forceinline__ void cp_async_commit() { asm volatile("cp.async.commit_group;" ::: "memory"); }
template <int N> __device__ __forceinline__ void cp_async_wait() { asm volatile("cp.async.wait_group %0;" :: "n"(N) : "memory"); }

struct Params {
    const __nv_bfloat16* m;
    const int* idx_in;
    const int* idx_out;
    const __nv_bfloat16* dist;
    const __nv_bfloat16* angle;
    const __nv_bfloat16* centers;
    const __nv_bfloat16* ang_freq;
    const __nv_bfloat16* w_rbf;
    const __nv_bfloat16* w_sbf;
    const __nv_bfloat16* w_down;
    const __nv_bfloat16* w_up;
    __nv_bfloat16* out;
    int E, T, nbins, ntiles, tile;
};

__device__ __noinline__ void slow_bin(const Params* pp, int bin) {
    const Params& p = *pp;
    for (int t = threadIdx.x; t < p.T; t += blockDim.x) {
        const int out = p.idx_out[t];
        if ((out >> NB_LOG) != bin) continue;
        const int in = p.idx_in[t];
        const float ang = ldbf(p.angle + t);
        float mrow[DE], rb[NR], cb[NL];
        for (int k = 0; k < DE; k++) mrow[k] = ldbf(p.m + (size_t)in * DE + k);
        float d = ldbf(p.dist + out);
        for (int r = 0; r < NR; r++) {
            float u = bf16r(d - ldbf(p.centers + r));
            u = bf16r(u * u);
            u = bf16r(-10.0f * u);
            rb[r] = bf16r(__expf(u));
        }
        for (int l = 0; l < NL; l++) cb[l] = bf16r(cosf(bf16r(ldbf(p.ang_freq + l) * ang)));
        for (int c = 0; c < DE; c++) {
            float md = 0.f, s = 0.f;
            for (int k = 0; k < DE; k++) md = fmaf(mrow[k], ldbf(p.w_down + k * DE + c), md);
            for (int r = 0; r < NR; r++)
                for (int l = 0; l < NL; l++) s = fmaf(rb[r] * cb[l], ldbf(p.w_sbf + (r * NL + l) * DE + c), s);
            atomicAdd(&g_ovf[(size_t)out * DE + c], md * s);
        }
    }
    __threadfence();
}

__device__ __forceinline__ int4 ld4_guard(const int* p, int i, int n, int fill) {
    if (i + 3 < n) return __ldcs(reinterpret_cast<const int4*>(p + i));
    int4 r;
    r.x = (i + 0 < n) ? p[i + 0] : fill;
    r.y = (i + 1 < n) ? p[i + 1] : fill;
    r.z = (i + 2 < n) ? p[i + 2] : fill;
    r.w = fill;
    return r;
}
__device__ __forceinline__ uint2 ld4h_guard(const unsigned short* p, int i, int n) {
    if (i + 3 < n) return __ldcs(reinterpret_cast<const uint2*>(p + i));
    uint32_t a = (i + 0 < n) ? p[i + 0] : 0u, b = (i + 1 < n) ? p[i + 1] : 0u, c = (i + 2 < n) ? p[i + 2] : 0u;
    return make_uint2(a | (b << 16), c);
}

__global__ void __launch_bounds__(P_NT, 1) k_partition(const __grid_constant__ Params p) {
    extern __shared__ __align__(16) unsigned char smem_raw[];
    uint2* stage = reinterpret_cast<uint2*>(smem_raw);
    int* hist = reinterpret_cast<int*>(smem_raw + (size_t)P_STAGE * 8);
    __shared__ int warp_sums[P_NT / 32];
    static_assert(BINS_PAD == 2 * P_NT, "two bins per thread in the scan");

    const int tid = threadIdx.x;
    const int lane = tid & 31, wid = tid >> 5;
    const unsigned short* ang16 = reinterpret_cast<const unsigned short*>(p.angle);

    if (blockIdx.x == 0 && wid == P_NT / 32 - 1) {
        const int g = lane >> 2, q = lane & 3;
        const unsigned short* wd = reinterpret_cast<const unsigned short*>(p.w_down);
        const unsigned short* wu = reinterpret_cast<const unsigned short*>(p.w_up);
        const unsigned short* ws = reinterpret_cast<const unsigned short*>(p.w_sbf);
        const unsigned short* wr = reinterpret_cast<const unsigned short*>(p.w_rbf);
        uint4 t;
        t.x = (uint32_t)wd[(2 * q) * DE + g] | ((uint32_t)wd[(2 * q + 1) * DE + g] << 16);
        t.y = (uint32_t)wd[(2 * q) * DE + g + 8] | ((uint32_t)wd[(2 * q + 1) * DE + g + 8] << 16);
        t.z = (uint32_t)wd[(2 * q + 8) * DE + g] | ((uint32_t)wd[(2 * q + 9) * DE + g] << 16);
        t.w = (uint32_t)wd[(2 * q + 8) * DE + g + 8] | ((uint32_t)wd[(2 * q + 9) * DE + g + 8] << 16);
        g_frag[lane] = t;
        const int cA = 2 * g, cB = 2 * g + 1;
        t.x = (uint32_t)wu[(2 * q) * DE + cA] | ((uint32_t)wu[(2 * q + 1) * DE + cA] << 16);
        t.y = (uint32_t)wu[(2 * q) * DE + cB] | ((uint32_t)wu[(2 * q + 1) * DE + cB] << 16);
        t.z = (uint32_t)wu[(2 * q + 8) * DE + cA] | ((uint32_t)wu[(2 * q + 9) * DE + cA] << 16);
        t.w = (uint32_t)wu[(2 * q + 8) * DE + cB] | ((uint32_t)wu[(2 * q + 9) * DE + cB] << 16);
        g_frag[32 + lane] = t;
        uint32_t sb[NL][2];
#pragma unroll
        for (int l = 0; l < NL; l++) {
            sb[l][0] = (uint32_t)ws[((2 * q) * NL + l) * DE + g] | ((uint32_t)ws[((2 * q + 1) * NL + l) * DE + g] << 16);
            sb[l][1] = (uint32_t)ws[((2 * q) * NL + l) * DE + g + 8] | ((uint32_t)ws[((2 * q + 1) * NL + l) * DE + g + 8] << 16);
        }
        g_frag[64 + lane] = make_uint4(sb[0][0], sb[0][1], sb[1][0], sb[1][1]);
        t.x = sb[2][0]; t.y = sb[2][1];
        t.z = (uint32_t)wr[(2 * q) * DE + cA] | ((uint32_t)wr[(2 * q + 1) * DE + cA] << 16);
        t.w = (uint32_t)wr[(2 * q) * DE + cB] | ((uint32_t)wr[(2 * q + 1) * DE + cB] << 16);
        g_frag[96 + lane] = t;
    }

    int4 O[P_PER / 4];
    int tile = blockIdx.x;
    if (tile < p.ntiles) {
        const int base = tile * p.tile, n = min(p.tile, p.T - base);
#pragma unroll
        for (int v = 0; v < P_PER / 4; v++) O[v] = ld4_guard(p.idx_out + base, (v * P_NT + tid) * 4, n, -1);
    }
    reinterpret_cast<int2*>(hist)[tid] = make_int2(0, 0);
    if (tid == 0) hist[BINS_PAD] = 0;
    for (; tile < p.ntiles; tile += gridDim.x) {
        const int base = tile * p.tile, n = min(p.tile, p.T - base);
        __syncthreads();
#pragma unroll
        for (int v = 0; v < P_PER / 4; v++) {
            atomicAdd(&hist[min((uint32_t)O[v].x >> NB_LOG, (uint32_t)BINS_PAD)], 1);
            atomicAdd(&hist[min((uint32_t)O[v].y >> NB_LOG, (uint32_t)BINS_PAD)], 1);
            atomicAdd(&hist[min((uint32_t)O[v].z >> NB_LOG, (uint32_t)BINS_PAD)], 1);
            atomicAdd(&hist[min((uint32_t)O[v].w >> NB_LOG, (uint32_t)BINS_PAD)], 1);
        }
        int4 I[P_PER / 4];
        uint2 A[P_PER / 4];
#pragma unroll
        for (int v = 0; v < P_PER / 4; v++) {
            I[v] = ld4_guard(p.idx_in + base, (v * P_NT + tid) * 4, n, 0);
            A[v] = ld4h_guard(ang16 + base, (v * P_NT + tid) * 4, n);
        }
        __syncthreads();
        const int2 c2 = reinterpret_cast<int2*>(hist)[tid];
        const int pc0 = (c2.x + 3) & ~3, pc1 = (c2.y + 3) & ~3;
        int g0 = 0, g1 = 0;
        if (pc0) g0 = atomicAdd(&g_cursor[2 * tid], pc0);
        if (pc1) g1 = atomicAdd(&g_cursor[2 * tid + 1], pc1);
        const int s = pc0 + pc1;
        int inc = s;
#pragma unroll
        for (int o = 1; o < 32; o <<= 1) {
            int t = __shfl_up_sync(0xffffffffu, inc, o);
            if (lane >= o) inc += t;
        }
        if (lane == 31) warp_sums[wid] = inc;
        asm volatile("cp.async.bulk.wait_group.read 0;" ::: "memory");
        __syncthreads();
        int woff;
        {
            int ws = warp_sums[lane];
            int winc = ws;
#pragma unroll
            for (int o = 1; o < 32; o <<= 1) {
                int t = __shfl_up_sync(0xffffffffu, winc, o);
                if (lane >= o) winc += t;
            }
            woff = __shfl_sync(0xffffffffu, winc - ws, wid);
        }
        const int e0 = woff + inc - s, e1 = e0 + pc0;
        reinterpret_cast<int2*>(hist)[tid] = make_int2(e0, e1);
        if (tid == 0) hist[BINS_PAD] = P_STAGE;
        for (int k = c2.x; k < pc0; k++) stage[e0 + k] = make_uint2(0u, 0xffffffffu);
        for (int k = c2.y; k < pc1; k++) stage[e1 + k] = make_uint2(0u, 0xffffffffu);
        __syncthreads();
#pragma unroll
        for (int v = 0; v < P_PER / 4; v++) {
            const uint32_t o[4] = {(uint32_t)O[v].x, (uint32_t)O[v].y, (uint32_t)O[v].z, (uint32_t)O[v].w};
            const uint32_t in[4] = {(uint32_t)I[v].x, (uint32_t)I[v].y, (uint32_t)I[v].z, (uint32_t)I[v].w};
            const uint32_t an[4] = {A[v].x & 0xffffu, A[v].x >> 16, A[v].y & 0xffffu, A[v].y >> 16};
#pragma unroll
            for (int u = 0; u < 4; u++) {
                int pos = atomicAdd(&hist[min(o[u] >> NB_LOG, (uint32_t)BINS_PAD)], 1);
                stage[min(pos, P_STAGE - 1)] = make_uint2((in[u] << 5) | (0x1000000u << (o[u] & 7)), an[u] | ((o[u] & 255u) << 16));
            }
        }
        {
            const int nt = tile + gridDim.x;
            if (nt < p.ntiles) {
                const int nbase = nt * p.tile, nn = min(p.tile, p.T - nbase);
#pragma unroll
                for (int v = 0; v < P_PER / 4; v++) O[v] = ld4_guard(p.idx_out + nbase, (v * P_NT + tid) * 4, nn, -1);
            }
        }
        asm volatile("fence.proxy.async.shared::cta;" ::: "memory");
        __syncthreads();
        if (pc0 && g0 + pc0 <= CAPG)
            asm volatile("cp.async.bulk.global.shared::cta.bulk_group [%0], [%1], %2;"
                         :: "l"(g_records + (size_t)(2 * tid) * CAPG + g0), "r"(smem_u32(stage + e0)), "r"(pc0 * 8) : "memory");
        if (pc1 && g1 + pc1 <= CAPG)
            asm volatile("cp.async.bulk.global.shared::cta.bulk_group [%0], [%1], %2;"
                         :: "l"(g_records + (size_t)(2 * tid + 1) * CAPG + g1), "r"(smem_u32(stage + e1)), "r"(pc1 * 8) : "memory");
        asm volatile("cp.async.bulk.commit_group;" ::: "memory");
        reinterpret_cast<int2*>(hist)[tid] = make_int2(0, 0);
        if (tid == 0) hist[BINS_PAD] = 0;
    }
    asm volatile("cp.async.bulk.wait_group 0;" ::: "memory");
}

constexpr int NOCT = CAPS / 8;
constexpr int SM_IDX = 0;
constexpr int SM_CA = SM_IDX + (CAPS + 32) * 4;
constexpr int SM_CB = SM_CA + NOCT * 16;
constexpr int SM_C2 = SM_CB + NOCT * 16;
constexpr int SM_OH = SM_C2 + (NOCT + 4) * 16;
constexpr int SM_RING = SM_OH + (NOCT + 8) * 8;
constexpr int SM_TOTAL = SM_RING + (G_NT / 32) * G_STAGES * 1024;

__device__ __forceinline__ uint2 lds64(uint32_t a) { uint2 v; asm volatile("ld.shared.v2.u32 {%0,%1}, [%2];" : "=r"(v.x), "=r"(v.y) : "r"(a) : "memory"); return v; }

__global__ void __launch_bounds__(G_NT, G_BLOCKS) k_gather(const __grid_constant__ Params p) {
    extern __shared__ __align__(128) unsigned char smem_raw[];
    uint32_t* sidx = reinterpret_cast<uint32_t*>(smem_raw + SM_IDX);
    uint4* scA = reinterpret_cast<uint4*>(smem_raw + SM_CA);
    uint4* scB = reinterpret_cast<uint4*>(smem_raw + SM_CB);
    unsigned short* sang = reinterpret_cast<unsigned short*>(smem_raw + SM_C2);
    uint2* soh = reinterpret_cast<uint2*>(smem_raw + SM_OH);
    __shared__ int cnts[NB + 32];
    __shared__ int gstart[NGRP + 1];
    __shared__ int warp_sums[NB / 32];

    const int tid = threadIdx.x;
    const int lane = tid & 31, wid = tid >> 5;
    const int bin = blockIdx.x;
    const int total = g_cursor[bin];
    bool ovf = total > CAPG;
    const int n = ovf ? 0 : total;

    const uint4* rec = reinterpret_cast<const uint4*>(g_records + (size_t)bin * CAPG) + tid;
    uint4 r[G_PER / 2];
#pragma unroll
    for (int j = 0; j < G_PER / 2; j++) {
        r[j] = make_uint4(0u, 0xffffffffu, 0u, 0xffffffffu);
        if ((j * G_NT + tid) * 2 < n) r[j] = __ldcs(rec + j * G_NT);
    }
    if (tid < NB) cnts[tid] = 0;
    for (int i = tid; i < (G_NT / 32) * G_STAGES * 64; i += G_NT)
        reinterpret_cast<uint4*>(smem_raw + SM_RING)[i] = make_uint4(0u, 0u, 0u, 0u);
    const unsigned short* fq = reinterpret_cast<const unsigned short*>(p.ang_freq);
    const uint32_t f0 = (uint32_t)fq[0] * 0x10001u, f1 = (uint32_t)fq[1] * 0x10001u, f2 = (uint32_t)fq[2] * 0x10001u;
    const uint32_t fmaxp = max(max(f0 & 0x7fff7fffu, f1 & 0x7fff7fffu), f2 & 0x7fff7fffu);
    const uint32_t dkey = NB + lane;
    __syncthreads();
    if (tid == 0) g_cursor[bin] = 0;
#pragma unroll
    for (int j = 0; j < G_PER / 2; j++) {
        atomicAdd(&cnts[min(r[j].y >> 16, dkey)], 1);
        atomicAdd(&cnts[min(r[j].w >> 16, dkey)], 1);
    }
    __syncthreads();
    int c = 0, inc = 0, cp = 0, npad = 0;
    if (tid < NB) {
        c = cnts[tid];
        int gt = c;
        gt += __shfl_xor_sync(0xffffffffu, gt, 1);
        gt += __shfl_xor_sync(0xffffffffu, gt, 2);
        gt += __shfl_xor_sync(0xffffffffu, gt, 4);
        npad = ((gt + 31) & ~31) - gt;
        cp = c + (((lane & 7) == 7) ? npad : 0);
        inc = cp;
#pragma unroll
        for (int o = 1; o < 32; o <<= 1) {
            int t = __shfl_up_sync(0xffffffffu, inc, o);
            if (lane >= o) inc += t;
        }
        if (lane == 31) warp_sums[wid] = inc;
    }
    __syncthreads();
    {
        int woff = 0, tot = 0;
#pragma unroll
        for (int w = 0; w < NB / 32; w++) { woff += (w < wid) ? warp_sums[w] : 0; tot += warp_sums[w]; }
        ovf = ovf || (tot > CAPS);
        if (tid < NB) {
            const int st = ovf ? 0 : woff + inc - cp;
            cnts[tid] = ovf ? CAPS : st;
            if ((lane & 7) == 0) gstart[tid >> 3] = st;
            if (tid == NB - 1) gstart[NGRP] = ovf ? 0 : tot;
            if (tid < 32) cnts[NB + tid] = CAPS;
            const int gend = __shfl_sync(0xffffffffu, woff + inc, lane | 7);
            if (!ovf) {
#pragma unroll
                for (int k = 0; k < 4; k++) {
                    const int kk = (lane & 7) + 8 * k;
                    if (kk < npad) { sidx[gend - 1 - kk] = 0u; sang[gend - 1 - kk] = 0; }
                }
            }
        }
    }
    __syncthreads();
#pragma unroll
    for (int j = 0; j < G_PER / 2; j++) {
        {
            const int pos = min(atomicAdd(&cnts[min(r[j].y >> 16, dkey)], 1), CAPS);
            sidx[pos] = r[j].x;
            sang[pos] = (unsigned short)r[j].y;
        }
        {
            const int pos = min(atomicAdd(&cnts[min(r[j].w >> 16, dkey)], 1), CAPS);
            sidx[pos] = r[j].z;
            sang[pos] = (unsigned short)r[j].w;
        }
    }
    if (ovf) slow_bin(&p, bin);
    __syncthreads();

    const int g = lane >> 2, q = lane & 3;
    constexpr int GPW = NGRP / (G_NT / 32);
    const int grp0 = wid * GPW;
    const int wbeg = gstart[grp0], wend = gstart[grp0 + GPW];
    const unsigned char* mb = reinterpret_cast<const unsigned char*>(p.m);
    const uint32_t sbase = smem_u32(smem_raw);

    const uint32_t ring = sbase + SM_RING + wid * (G_STAGES * 1024);
    const int cj = lane >> 1;
    const int crow = (cj >> 2) * 2 + (cj & 1) + ((cj >> 1) & 1) * 8;
    const uint32_t cdst = ring + (uint32_t)(crow * 32 + (((lane ^ (crow >> 2)) & 1) * 16));
    const unsigned char* msrc = mb + (lane & 1) * 16;
    const int lrow = (lane >> 4) * 8 + (lane & 7);
    const uint32_t lsrc = ring + (uint32_t)(lrow * 32 + ((((lane >> 3) ^ (lrow >> 2)) & 1) * 16));

    uint32_t iaddr = sbase + SM_IDX + (wbeg + 2 * cj) * 4;
    const uint32_t iend = sbase + SM_IDX + wend * 4;
    uint32_t ioff = 0;
#pragma unroll
    for (int k = 0; k < G_STAGES - 1; k++) {
        if (iaddr < iend) {
            const uint2 w = lds64(iaddr);
            cp_async_row(cdst + ioff, msrc, w.x);
            cp_async_row(cdst + ioff + 512, msrc, w.y);
        }
        cp_async_commit();
        iaddr += 128; ioff += 1024;
    }

    {
        const int noct = gstart[NGRP] >> 3;
        for (int i = tid; i < noct; i += G_NT) {
            const uint4 an = reinterpret_cast<const uint4*>(sang)[i];
            const uint4 w0 = reinterpret_cast<const uint4*>(sidx)[2 * i];
            const uint4 w1 = reinterpret_cast<const uint4*>(sidx)[2 * i + 1];
            soh[i] = make_uint2(prmt(prmt(w0.x, w0.z, 0x0073), prmt(w1.x, w1.z, 0x0073), 0x5410),
                                prmt(prmt(w0.y, w0.w, 0x0073), prmt(w1.y, w1.w, 0x0073), 0x5410));
            const uint32_t aA0 = prmt(an.x, an.y, 0x5410), aA1 = prmt(an.z, an.w, 0x5410);
            const uint32_t aB0 = prmt(an.x, an.y, 0x7632), aB1 = prmt(an.z, an.w, 0x7632);
            const uint32_t amax = __vmaxu2(__vmaxu2(an.x & 0x7fff7fffu, an.y & 0x7fff7fffu), __vmaxu2(an.z & 0x7fff7fffu, an.w & 0x7fff7fffu));
            const uint32_t t = mul_bf16x2(amax, fmaxp);
            uint4 oA, oB, o2;
            if ((t >> 16) < 0x4300u && (t & 0xffffu) < 0x4300u) {
                oA.x = cos_fast_bf16x2(mul_bf16x2(aA0, f0)); oA.y = cos_fast_bf16x2(mul_bf16x2(aA1, f0));
                oA.z = cos_fast_bf16x2(mul_bf16x2(aA0, f1)); oA.w = cos_fast_bf16x2(mul_bf16x2(aA1, f1));
                oB.x = cos_fast_bf16x2(mul_bf16x2(aB0, f0)); oB.y = cos_fast_bf16x2(mul_bf16x2(aB1, f0));
                oB.z = cos_fast_bf16x2(mul_bf16x2(aB0, f1)); oB.w = cos_fast_bf16x2(mul_bf16x2(aB1, f1));
                o2.x = cos_fast_bf16x2(mul_bf16x2(aA0, f2)); o2.y = cos_fast_bf16x2(mul_bf16x2(aA1, f2));
                o2.z = cos_fast_bf16x2(mul_bf16x2(aB0, f2)); o2.w = cos_fast_bf16x2(mul_bf16x2(aB1, f2));
            } else {
                oA.x = cos_slow_bf16x2(mul_bf16x2(aA0, f0)); oA.y = cos_slow_bf16x2(mul_bf16x2(aA1, f0));
                oA.z = cos_slow_bf16x2(mul_bf16x2(aA0, f1)); oA.w = cos_slow_bf16x2(mul_bf16x2(aA1, f1));
                oB.x = cos_slow_bf16x2(mul_bf16x2(aB0, f0)); oB.y = cos_slow_bf16x2(mul_bf16x2(aB1, f0));
                oB.z = cos_slow_bf16x2(mul_bf16x2(aB0, f1)); oB.w = cos_slow_bf16x2(mul_bf16x2(aB1, f1));
                o2.x = cos_slow_bf16x2(mul_bf16x2(aA0, f2)); o2.y = cos_slow_bf16x2(mul_bf16x2(aA1, f2));
                o2.z = cos_slow_bf16x2(mul_bf16x2(aB0, f2)); o2.w = cos_slow_bf16x2(mul_bf16x2(aB1, f2));
            }
            scA[i] = oA;
            scB[i] = oB;
            reinterpret_cast<uint4*>(sang)[i] = o2;
        }
    }

    uint32_t adown[4], aup[4], asbf[NL][2], arb[2];
    {
        const uint4* fr = reinterpret_cast<const uint4*>(g_frag) + lane;
        const uint4 t0 = __ldg(fr), t1 = __ldg(fr + 32), t2 = __ldg(fr + 64), t3 = __ldg(fr + 96);
        adown[0] = t0.x; adown[1] = t0.y; adown[2] = t0.z; adown[3] = t0.w;
        aup[0] = t1.x; aup[1] = t1.y; aup[2] = t1.z; aup[3] = t1.w;
        asbf[0][0] = t2.x; asbf[0][1] = t2.y; asbf[1][0] = t2.z; asbf[1][1] = t2.w;
        asbf[2][0] = t3.x; asbf[2][1] = t3.y; arb[0] = t3.z; arb[1] = t3.w;
    }
    const uint32_t cen = reinterpret_cast<const uint32_t*>(p.centers)[q];

    const int ew = bin * NB + grp0 * 8;
    const unsigned short* pdist = reinterpret_cast<const unsigned short*>(p.dist) + ew + g;
    const uint32_t moff0 = (uint32_t)(ew + 2 * q) * 32u + 4u * g;
    const int nleft = p.E - ew;
    uint32_t dgn = (g < nleft) ? (uint32_t)pdist[0] : 0u;
    uint32_t man = (2 * q < nleft) ? __ldg(reinterpret_cast<const uint32_t*>(mb + moff0)) : 0u;
    uint32_t mbn = (2 * q + 1 < nleft) ? __ldg(reinterpret_cast<const uint32_t*>(mb + moff0 + 32)) : 0u;
    __syncthreads();

    uint2 wnext = make_uint2(0u, 0u);
    if (iaddr < iend) wnext = lds64(iaddr);
    uint32_t ac = sbase + SM_CA + ((wbeg >> 3) + q) * 16;
    uint32_t aoh = sbase + SM_OH + ((wbeg >> 3) + q) * 8;
    uint2 ohnext = lds64(aoh);
    uint4 cA = make_uint4(0u, 0u, 0u, 0u), cB = cA, c2 = cA;
#pragma unroll 1
    for (int gi = 0; gi < GPW; gi++) {
        const uint32_t aend = sbase + SM_OH + (uint32_t)gstart[grp0 + gi + 1];
        const uint32_t moff = moff0 + gi * 256;
        const bool va = gi * 8 + 2 * q < nleft, vb = gi * 8 + 2 * q + 1 < nleft;
        const uint32_t dg = dgn, ma = man, mbv = mbn;
        if (gi + 1 < GPW) {
            dgn = (gi * 8 + 8 + g < nleft) ? (uint32_t)pdist[gi * 8 + 8] : 0u;
            man = (gi * 8 + 8 + 2 * q < nleft) ? __ldg(reinterpret_cast<const uint32_t*>(mb + moff + 256)) : 0u;
            mbn = (gi * 8 + 9 + 2 * q < nleft) ? __ldg(reinterpret_cast<const uint32_t*>(mb + moff + 288)) : 0u;
        }

        float D[NL][4];
#pragma unroll
        for (int l = 0; l < NL; l++)
#pragma unroll
            for (int c4 = 0; c4 < 4; c4++) D[l][c4] = 0.f;
#pragma unroll 1
        while (aoh < aend) {
            cp_async_row(cdst + ioff, msrc, wnext.x);
            cp_async_row(cdst + ioff + 512, msrc, wnext.y);
            cp_async_commit();
            iaddr += 128; ioff = (ioff == (G_STAGES - 1) * 1024) ? 0 : ioff + 1024;
            wnext = make_uint2(0u, 0u);
            if (iaddr < iend) wnext = lds64(iaddr);
            const uint32_t kA = (ohnext.x >> g) & 0x01010101u, kB = (ohnext.y >> g) & 0x01010101u;
            asm volatile("{ .reg .pred pa, pb, pc; setp.ne.u32 pa, %13, 0; setp.ne.u32 pb, %14, 0; or.pred pc, pa, pb;\n\t"
                         "@pa ld.shared.v4.u32 {%0,%1,%2,%3}, [%12];\n\t"
                         "@pb ld.shared.v4.u32 {%4,%5,%6,%7}, [%12+%15];\n\t"
                         "@pc ld.shared.v4.u32 {%8,%9,%10,%11}, [%12+%16]; }"
                         : "+r"(cA.x), "+r"(cA.y), "+r"(cA.z), "+r"(cA.w), "+r"(cB.x), "+r"(cB.y), "+r"(cB.z), "+r"(cB.w),
                           "+r"(c2.x), "+r"(c2.y), "+r"(c2.z), "+r"(c2.w)
                         : "r"(ac), "r"(kA), "r"(kB), "n"(SM_CB - SM_CA), "n"(SM_C2 - SM_CA) : "memory");
            ac += 64; aoh += 32;
            ohnext = lds64(aoh);
            const uint32_t kA0 = prmt(kA, 0, 0x4140) * 0x3F80u, kA1 = prmt(kA, 0, 0x4342) * 0x3F80u;
            const uint32_t kB0 = prmt(kB, 0, 0x4140) * 0x3F80u, kB1 = prmt(kB, 0, 0x4342) * 0x3F80u;
            cp_async_wait<G_STAGES - 1>();
            __syncwarp();
            uint32_t a[4], b[4];
            ldsm_x4_trans(a, lsrc + ioff);
            ldsm_x4_trans(b, lsrc + ioff + 512);
            mma16816(D[0], a, mul_bf16x2(cA.x, kA0), mul_bf16x2(cA.y, kA1));
            mma16816(D[1], a, mul_bf16x2(cA.z, kA0), mul_bf16x2(cA.w, kA1));
            mma16816(D[2], a, mul_bf16x2(c2.x, kA0), mul_bf16x2(c2.y, kA1));
            mma16816(D[0], b, mul_bf16x2(cB.x, kB0), mul_bf16x2(cB.y, kB1));
            mma16816(D[1], b, mul_bf16x2(cB.z, kB0), mul_bf16x2(cB.w, kB1));
            mma16816(D[2], b, mul_bf16x2(c2.z, kB0), mul_bf16x2(c2.w, kB1));
        }
        const uint32_t brbf = rbf_bf16x2(dg * 0x10001u, cen);
        float agg[4] = {0.f, 0.f, 0.f, 0.f};
#pragma unroll
        for (int l = 0; l < NL; l++) {
            const uint32_t h0 = movm(pack_bf16(D[l][0], D[l][1]));
            const uint32_t h1 = movm(pack_bf16(D[l][2], D[l][3]));
            float S[4] = {0.f, 0.f, 0.f, 0.f};
            float G[4] = {0.f, 0.f, 0.f, 0.f};
            mma16816(S, adown, h0, h1);
            mma1688(G, asbf[l], brbf);
#pragma unroll
            for (int c4 = 0; c4 < 4; c4++) agg[c4] = fmaf(S[c4], G[c4], agg[c4]);
        }
        if (ovf) {
            const int ea = ew + gi * 8 + 2 * q;
            if (va) {
                float* pa = g_ovf + (size_t)ea * DE + g;
                agg[0] += __ldcg(pa); agg[2] += __ldcg(pa + 8);
                pa[0] = 0.f; pa[8] = 0.f;
            }
            if (vb) {
                float* pb = g_ovf + (size_t)(ea + 1) * DE + g;
                agg[1] += __ldcg(pb); agg[3] += __ldcg(pb + 8);
                pb[0] = 0.f; pb[8] = 0.f;
            }
        }
        {
            const uint32_t h0 = movm(pack_bf16(agg[0], agg[1]));
            const uint32_t h1 = movm(pack_bf16(agg[2], agg[3]));
            float U[4] = {0.f, 0.f, 0.f, 0.f};
            float R[4] = {0.f, 0.f, 0.f, 0.f};
            mma16816(U, aup, h0, h1);
            mma1688(R, arb, brbf);
            uint32_t oa = pack_bf16(fmaf(U[0], R[0], bf16lo(ma)), fmaf(U[2], R[2], bf16hi(ma)));
            uint32_t ob = pack_bf16(fmaf(U[1], R[1], bf16lo(mbv)), fmaf(U[3], R[3], bf16hi(mbv)));
            unsigned char* ob8 = reinterpret_cast<unsigned char*>(p.out);
            if (va) *reinterpret_cast<uint32_t*>(ob8 + moff) = oa;
            if (vb) *reinterpret_cast<uint32_t*>(ob8 + moff + 32) = ob;
        }
    }
}

}

extern "C" void kernel_launch(void* const* d_in, const int* in_sizes, int n_in,
                              void* d_out, int out_size) {
    Params p;
    p.m = (const __nv_bfloat16*)d_in[0];
    p.idx_in = (const int*)d_in[1];
    p.idx_out = (const int*)d_in[2];
    p.dist = (const __nv_bfloat16*)d_in[3];
    p.angle = (const __nv_bfloat16*)d_in[4];
    p.centers = (const __nv_bfloat16*)d_in[5];
    p.ang_freq = (const __nv_bfloat16*)d_in[6];
    p.w_rbf = (const __nv_bfloat16*)d_in[7];
    p.w_sbf = (const __nv_bfloat16*)d_in[8];
    p.w_down = (const __nv_bfloat16*)d_in[9];
    p.w_up = (const __nv_bfloat16*)d_in[10];
    p.out = (__nv_bfloat16*)d_out;
    p.E = in_sizes[3];
    p.T = in_sizes[1];
    p.nbins = (p.E + NB - 1) / NB;

    const int smem1 = P_STAGE * 8 + (BINS_PAD + 4) * 4;
    const int smem2 = SM_TOTAL;
    static int nsm = 0;
    if (!nsm) {
        cudaFuncSetAttribute(k_partition, cudaFuncAttributeMaxDynamicSharedMemorySize, smem1);
        cudaFuncSetAttribute(k_gather, cudaFuncAttributeMaxDynamicSharedMemorySize, smem2);
        int dev = 0;
        cudaGetDevice(&dev);
        cudaDeviceGetAttribute(&nsm, cudaDevAttrMultiProcessorCount, dev);
    }
    long long per_sm = ((long long)p.T + nsm - 1) / nsm;
    int k = (int)((per_sm + P_TILE_MAX - 1) / P_TILE_MAX);
    if (k < 1) k = 1;
    long long tile = ((long long)p.T + (long long)k * nsm - 1) / ((long long)k * nsm);
    tile = (tile + 15) & ~15LL;
    if (tile > P_TILE_MAX) tile = P_TILE_MAX;
    if (tile < 16) tile = 16;
    p.tile = (int)tile;
    p.ntiles = (int)(((long long)p.T + tile - 1) / tile);
    int g1 = p.ntiles < nsm ? p.ntiles : nsm;
    if (g1 < 1) g1 = 1;
    k_partition<<<g1, P_NT, smem1>>>(p);
    k_gather<<<p.nbins, G_NT, smem2>>>(p);
}
```

```cpp
#include <cuda_runtime.h>
#include <cuda_bf16.h>
#include <stdint.h>

namespace {

constexpr int DE = 16;
constexpr int NR = 8;
constexpr int NL = 3;

constexpr int NB_LOG = 8;
constexpr int NB = 1 << NB_LOG;
constexpr int MAX_E = 400000;
constexpr int MAX_BINS = (MAX_E + NB - 1) / NB;
constexpr int BINS_PAD = 2048;
constexpr int CAPG = 5120;

constexpr int P_NT = 1024;
constexpr int P_PER = 16;
constexpr int P_TILE_MAX = P_NT * P_PER;
constexpr int P_STAGE = P_TILE_MAX + 3 * MAX_BINS + 16;

#define CFG_G_NT 256
#define CFG_G_BLOCKS 3
#define CFG_G_STAGES 2
#define CFG_STAGGER_NS 6000
#define CFG_PREFETCH 1
constexpr int G_NT = CFG_G_NT;
constexpr int G_BLOCKS = CFG_G_BLOCKS;
constexpr int G_PER = CAPG / G_NT;
constexpr int NGRP = NB / 8;
constexpr int CAPS = 5120;
constexpr int G_STAGES = CFG_G_STAGES;

__device__ uint2 g_records[(size_t)MAX_BINS * CAPG];
__device__ int g_cursor[BINS_PAD];
__device__ uint4 g_frag[4 * 32];
__device__ float g_ovf[(size_t)MAX_BINS * NB * DE];

__device__ __forceinline__ float bf16r(float x) { return __bfloat162float(__float2bfloat16_rn(x)); }
__device__ __forceinline__ float bf16lo(uint32_t v) { return __uint_as_float(v << 16); }
__device__ __forceinline__ float bf16hi(uint32_t v) { return __uint_as_float(v & 0xffff0000u); }
__device__ __forceinline__ float ldbf(const __nv_bfloat16* p) { return __bfloat162float(*p); }
__device__ __forceinline__ uint32_t smem_u32(const void* p) { return (uint32_t)__cvta_generic_to_shared(p); }

__device__ __forceinline__ uint32_t pack_bf16(float lo, float hi) {
    __nv_bfloat162 v = __floats2bfloat162_rn(lo, hi);
    return *reinterpret_cast<uint32_t*>(&v);
}
__device__ __forceinline__ uint32_t mul_bf16x2(uint32_t a, uint32_t b) {
    __nv_bfloat162 r = __hmul2(*reinterpret_cast<__nv_bfloat162*>(&a), *reinterpret_cast<__nv_bfloat162*>(&b));
    return *reinterpret_cast<uint32_t*>(&r);
}
__device__ __forceinline__ uint32_t sub_bf16x2(uint32_t a, uint32_t b) {
    __nv_bfloat162 r = __hsub2(*reinterpret_cast<__nv_bfloat162*>(&a), *reinterpret_cast<__nv_bfloat162*>(&b));
    return *reinterpret_cast<uint32_t*>(&r);
}
__device__ __forceinline__ uint32_t cos_fast_bf16x2(uint32_t x) {
    return pack_bf16(__cosf(bf16lo(x)), __cosf(bf16hi(x)));
}
__device__ __noinline__ uint32_t cos_slow_bf16x2(uint32_t x) {
    return pack_bf16(cosf(bf16lo(x)), cosf(bf16hi(x)));
}
__device__ __forceinline__ uint32_t rbf_bf16x2(uint32_t dd, uint32_t cc) {
    uint32_t t = sub_bf16x2(dd, cc);
    t = mul_bf16x2(t, t);
    t = mul_bf16x2(t, 0xC120C120u);
    return pack_bf16(__expf(bf16lo(t)), __expf(bf16hi(t)));
}

__device__ __forceinline__ void mma16816(float* d, const uint32_t* a, uint32_t b0, uint32_t b1) {
    asm volatile("mma.sync.aligned.m16n8k16.row.col.f32.bf16.bf16.f32 {%0,%1,%2,%3}, {%4,%5,%6,%7}, {%8,%9}, {%0,%1,%2,%3};"
                 : "+f"(d[0]), "+f"(d[1]), "+f"(d[2]), "+f"(d[3])
                 : "r"(a[0]), "r"(a[1]), "r"(a[2]), "r"(a[3]), "r"(b0), "r"(b1));
}
__device__ __forceinline__ void mma1688(float* d, const uint32_t* a, uint32_t b) {
    asm volatile("mma.sync.aligned.m16n8k8.row.col.f32.bf16.bf16.f32 {%0,%1,%2,%3}, {%4,%5}, {%6}, {%0,%1,%2,%3};"
                 : "+f"(d[0]), "+f"(d[1]), "+f"(d[2]), "+f"(d[3])
                 : "r"(a[0]), "r"(a[1]), "r"(b));
}
__device__ __forceinline__ uint32_t movm(uint32_t a) {
    uint32_t d;
    asm volatile("movmatrix.sync.aligned.m8n8.trans.b16 %0, %1;" : "=r"(d) : "r"(a));
    return d;
}
__device__ __forceinline__ uint32_t prmt(uint32_t a, uint32_t b, uint32_t sel) {
    uint32_t d;
    asm("prmt.b32 %0, %1, %2, %3;" : "=r"(d) : "r"(a), "r"(b), "r"(sel));
    return d;
}
__device__ __forceinline__ void ldsm_x4_trans(uint32_t* r, uint32_t addr) {
    asm volatile("ldmatrix.sync.aligned.m8n8.x4.trans.shared.b16 {%0,%1,%2,%3}, [%4];"
                 : "=r"(r[0]), "=r"(r[1]), "=r"(r[2]), "=r"(r[3]) : "r"(addr) : "memory");
}
__device__ __forceinline__ void cp_async_row(uint32_t dst, const unsigned char* base, uint32_t w) {
    uint64_t addr;
    asm("mad.wide.u32 %0, %1, 1, %2;" : "=l"(addr) : "r"(w & 0xffffffu), "l"(base));
    asm volatile("{ .reg .pred p; setp.gt.u32 p, %2, 0xffffff; @p cp.async.cg.shared.global [%0], [%1], 16; }" :: "r"(dst), "l"(addr), "r"(w) : "memory");
}
__device__ __forceinline__ void cp_async_commit() { asm volatile("cp.async.commit_group;" ::: "memory"); }
template <int N> __device__ __forceinline__ void cp_async_wait() { asm volatile("cp.async.wait_group %0;" :: "n"(N) : "memory"); }

struct Params {
    const __nv_bfloat16* m;
    const int* idx_in;
    const int* idx_out;
    const __nv_bfloat16* dist;
    const __nv_bfloat16* angle;
    const __nv_bfloat16* centers;
    const __nv_bfloat16* ang_freq;
    const __nv_bfloat16* w_rbf;
    const __nv_bfloat16* w_sbf;
    const __nv_bfloat16* w_down;
    const __nv_bfloat16* w_up;
    __nv_bfloat16* out;
    int E, T, nbins, ntiles, tile, nsm;
};

__device__ __noinline__ void slow_bin(const Params* pp, int bin) {
    const Params& p = *pp;
    for (int t = threadIdx.x; t < p.T; t += blockDim.x) {
        const int out = p.idx_out[t];
        if ((out >> NB_LOG) != bin) continue;
        const int in = p.idx_in[t];
        const float ang = ldbf(p.angle + t);
        float mrow[DE], rb[NR], cb[NL];
        for (int k = 0; k < DE; k++) mrow[k] = ldbf(p.m + (size_t)in * DE + k);
        float d = ldbf(p.dist + out);
        for (int r = 0; r < NR; r++) {
            float u = bf16r(d - ldbf(p.centers + r));
            u = bf16r(u * u);
            u = bf16r(-10.0f * u);
            rb[r] = bf16r(__expf(u));
        }
        for (int l = 0; l < NL; l++) cb[l] = bf16r(cosf(bf16r(ldbf(p.ang_freq + l) * ang)));
        for (int c = 0; c < DE; c++) {
            float md = 0.f, s = 0.f;
            for (int k = 0; k < DE; k++) md = fmaf(mrow[k], ldbf(p.w_down + k * DE + c), md);
            for (int r = 0; r < NR; r++)
                for (int l = 0; l < NL; l++) s = fmaf(rb[r] * cb[l], ldbf(p.w_sbf + (r * NL + l) * DE + c), s);
            atomicAdd(&g_ovf[(size_t)out * DE + c], md * s);
        }
    }
    __threadfence();
}

__device__ __forceinline__ int4 ld4_guard(const int* p, int i, int n, int fill) {
    if (i + 3 < n) return __ldcs(reinterpret_cast<const int4*>(p + i));
    int4 r;
    r.x = (i + 0 < n) ? p[i + 0] : fill;
    r.y = (i + 1 < n) ? p[i + 1] : fill;
    r.z = (i + 2 < n) ? p[i + 2] : fill;
    r.w = fill;
    return r;
}
__device__ __forceinline__ uint2 ld4h_guard(const unsigned short* p, int i, int n) {
    if (i + 3 < n) return __ldcs(reinterpret_cast<const uint2*>(p + i));
    uint32_t a = (i + 0 < n) ? p[i + 0] : 0u, b = (i + 1 < n) ? p[i + 1] : 0u, c = (i + 2 < n) ? p[i + 2] : 0u;
    return make_uint2(a | (b << 16), c);
}

__global__ void __launch_bounds__(P_NT, 1) k_partition(const __grid_constant__ Params p) {
    extern __shared__ __align__(16) unsigned char smem_raw[];
    uint2* stage = reinterpret_cast<uint2*>(smem_raw);
    int* hist = reinterpret_cast<int*>(smem_raw + (size_t)P_STAGE * 8);
    __shared__ int warp_sums[P_NT / 32];
    static_assert(BINS_PAD == 2 * P_NT, "two bins per thread in the scan");

    const int tid = threadIdx.x;
    const int lane = tid & 31, wid = tid >> 5;
    const unsigned short* ang16 = reinterpret_cast<const unsigned short*>(p.angle);

    if (blockIdx.x == 0 && wid == P_NT / 32 - 1) {
        const int g = lane >> 2, q = lane & 3;
        const unsigned short* wd = reinterpret_cast<const unsigned short*>(p.w_down);
        const unsigned short* wu = reinterpret_cast<const unsigned short*>(p.w_up);
        const unsigned short* ws = reinterpret_cast<const unsigned short*>(p.w_sbf);
        const unsigned short* wr = reinterpret_cast<const unsigned short*>(p.w_rbf);
        uint4 t;
        t.x = (uint32_t)wd[(2 * q) * DE + g] | ((uint32_t)wd[(2 * q + 1) * DE + g] << 16);
        t.y = (uint32_t)wd[(2 * q) * DE + g + 8] | ((uint32_t)wd[(2 * q + 1) * DE + g + 8] << 16);
        t.z = (uint32_t)wd[(2 * q + 8) * DE + g] | ((uint32_t)wd[(2 * q + 9) * DE + g] << 16);
        t.w = (uint32_t)wd[(2 * q + 8) * DE + g + 8] | ((uint32_t)wd[(2 * q + 9) * DE + g + 8] << 16);
        g_frag[lane] = t;
        const int cA = 2 * g, cB = 2 * g + 1;
        t.x = (uint32_t)wu[(2 * q) * DE + cA] | ((uint32_t)wu[(2 * q + 1) * DE + cA] << 16);
        t.y = (uint32_t)wu[(2 * q) * DE + cB] | ((uint32_t)wu[(2 * q + 1) * DE + cB] << 16);
        t.z = (uint32_t)wu[(2 * q + 8) * DE + cA] | ((uint32_t)wu[(2 * q + 9) * DE + cA] << 16);
        t.w = (uint32_t)wu[(2 * q + 8) * DE + cB] | ((uint32_t)wu[(2 * q + 9) * DE + cB] << 16);
        g_frag[32 + lane] = t;
        uint32_t sb[NL][2];
#pragma unroll
        for (int l = 0; l < NL; l++) {
            sb[l][0] = (uint32_t)ws[((2 * q) * NL + l) * DE + g] | ((uint32_t)ws[((2 * q + 1) * NL + l) * DE + g] << 16);
            sb[l][1] = (uint32_t)ws[((2 * q) * NL + l) * DE + g + 8] | ((uint32_t)ws[((2 * q + 1) * NL + l) * DE + g + 8] << 16);
        }
        g_frag[64 + lane] = make_uint4(sb[0][0], sb[0][1], sb[1][0], sb[1][1]);
        t.x = sb[2][0]; t.y = sb[2][1];
        t.z = (uint32_t)wr[(2 * q) * DE + cA] | ((uint32_t)wr[(2 * q + 1) * DE + cA] << 16);
        t.w = (uint32_t)wr[(2 * q) * DE + cB] | ((uint32_t)wr[(2 * q + 1) * DE + cB] << 16);
        g_frag[96 + lane] = t;
    }

    int4 O[P_PER / 4];
    int tile = blockIdx.x;
    if (tile < p.ntiles) {
        const int base = tile * p.tile, n = min(p.tile, p.T - base);
#pragma unroll
        for (int v = 0; v < P_PER / 4; v++) O[v] = ld4_guard(p.idx_out + base, (v * P_NT + tid) * 4, n, -1);
    }
    reinterpret_cast<int2*>(hist)[tid] = make_int2(0, 0);
    if (tid == 0) hist[BINS_PAD] = 0;
    for (; tile < p.ntiles; tile += gridDim.x) {
        const int base = tile * p.tile, n = min(p.tile, p.T - base);
        __syncthreads();
#pragma unroll
        for (int v = 0; v < P_PER / 4; v++) {
            atomicAdd(&hist[min((uint32_t)O[v].x >> NB_LOG, (uint32_t)BINS_PAD)], 1);
            atomicAdd(&hist[min((uint32_t)O[v].y >> NB_LOG, (uint32_t)BINS_PAD)], 1);
            atomicAdd(&hist[min((uint32_t)O[v].z >> NB_LOG, (uint32_t)BINS_PAD)], 1);
            atomicAdd(&hist[min((uint32_t)O[v].w >> NB_LOG, (uint32_t)BINS_PAD)], 1);
        }
        int4 I[P_PER / 4];
        uint2 A[P_PER / 4];
#pragma unroll
        for (int v = 0; v < P_PER / 4; v++) {
            I[v] = ld4_guard(p.idx_in + base, (v * P_NT + tid) * 4, n, 0);
            A[v] = ld4h_guard(ang16 + base, (v * P_NT + tid) * 4, n);
        }
        __syncthreads();
        const int2 c2 = reinterpret_cast<int2*>(hist)[tid];
        const int pc0 = (c2.x + 3) & ~3, pc1 = (c2.y + 3) & ~3;
        int g0 = 0, g1 = 0;
        if (pc0) g0 = atomicAdd(&g_cursor[2 * tid], pc0);
        if (pc1) g1 = atomicAdd(&g_cursor[2 * tid + 1], pc1);
        const int s = pc0 + pc1;
        int inc = s;
#pragma unroll
        for (int o = 1; o < 32; o <<= 1) {
            int t = __shfl_up_sync(0xffffffffu, inc, o);
            if (lane >= o) inc += t;
        }
        if (lane == 31) warp_sums[wid] = inc;
        asm volatile("cp.async.bulk.wait_group.read 0;" ::: "memory");
        __syncthreads();
        int woff;
        {
            int ws = warp_sums[lane];
            int winc = ws;
#pragma unroll
            for (int o = 1; o < 32; o <<= 1) {
                int t = __shfl_up_sync(0xffffffffu, winc, o);
                if (lane >= o) winc += t;
            }
            woff = __shfl_sync(0xffffffffu, winc - ws, wid);
        }
        const int e0 = woff + inc - s, e1 = e0 + pc0;
        reinterpret_cast<int2*>(hist)[tid] = make_int2(e0, e1);
        if (tid == 0) hist[BINS_PAD] = P_STAGE;
        for (int k = c2.x; k < pc0; k++) stage[e0 + k] = make_uint2(0u, 0xffffffffu);
        for (int k = c2.y; k < pc1; k++) stage[e1 + k] = make_uint2(0u, 0xffffffffu);
        __syncthreads();
#pragma unroll
        for (int v = 0; v < P_PER / 4; v++) {
            const uint32_t o[4] = {(uint32_t)O[v].x, (uint32_t)O[v].y, (uint32_t)O[v].z, (uint32_t)O[v].w};
            const uint32_t in[4] = {(uint32_t)I[v].x, (uint32_t)I[v].y, (uint32_t)I[v].z, (uint32_t)I[v].w};
            const uint32_t an[4] = {A[v].x & 0xffffu, A[v].x >> 16, A[v].y & 0xffffu, A[v].y >> 16};
#pragma unroll
            for (int u = 0; u < 4; u++) {
                int pos = atomicAdd(&hist[min(o[u] >> NB_LOG, (uint32_t)BINS_PAD)], 1);
                stage[min(pos, P_STAGE - 1)] = make_uint2((in[u] << 5) | (0x1000000u << (o[u] & 7)), an[u] | ((o[u] & 255u) << 16));
            }
        }
        {
            const int nt = tile + gridDim.x;
            if (nt < p.ntiles) {
                const int nbase = nt * p.tile, nn = min(p.tile, p.T - nbase);
#pragma unroll
                for (int v = 0; v < P_PER / 4; v++) O[v] = ld4_guard(p.idx_out + nbase, (v * P_NT + tid) * 4, nn, -1);
            }
        }
        asm volatile("fence.proxy.async.shared::cta;" ::: "memory");
        __syncthreads();
        if (pc0 && g0 + pc0 <= CAPG)
            asm volatile("cp.async.bulk.global.shared::cta.bulk_group [%0], [%1], %2;"
                         :: "l"(g_records + (size_t)(2 * tid) * CAPG + g0), "r"(smem_u32(stage + e0)), "r"(pc0 * 8) : "memory");
        if (pc1 && g1 + pc1 <= CAPG)
            asm volatile("cp.async.bulk.global.shared::cta.bulk_group [%0], [%1], %2;"
                         :: "l"(g_records + (size_t)(2 * tid + 1) * CAPG + g1), "r"(smem_u32(stage + e1)), "r"(pc1 * 8) : "memory");
        asm volatile("cp.async.bulk.commit_group;" ::: "memory");
        reinterpret_cast<int2*>(hist)[tid] = make_int2(0, 0);
        if (tid == 0) hist[BINS_PAD] = 0;
    }
    asm volatile("cp.async.bulk.wait_group 0;" ::: "memory");
}

constexpr int NOCT = CAPS / 8;
constexpr int SM_IDX = 0;
constexpr int SM_CA = SM_IDX + (CAPS + 32) * 4;
constexpr int SM_CB = SM_CA + NOCT * 16;
constexpr int SM_C2 = SM_CB + NOCT * 16;
constexpr int SM_OH = SM_C2 + (NOCT + 4) * 16;
constexpr int SM_RING = SM_OH + (NOCT + 8) * 8;
constexpr int SM_TOTAL = SM_RING + (G_NT / 32) * G_STAGES * 1024;

__device__ __forceinline__ uint2 lds64(uint32_t a) { uint2 v; asm volatile("ld.shared.v2.u32 {%0,%1}, [%2];" : "=r"(v.x), "=r"(v.y) : "r"(a) : "memory"); return v; }

__global__ void __launch_bounds__(G_NT, G_BLOCKS) k_gather(const __grid_constant__ Params p) {
    extern __shared__ __align__(128) unsigned char smem_raw[];
    uint32_t* sidx = reinterpret_cast<uint32_t*>(smem_raw + SM_IDX);
    uint4* scA = reinterpret_cast<uint4*>(smem_raw + SM_CA);
    uint4* scB = reinterpret_cast<uint4*>(smem_raw + SM_CB);
    unsigned short* sang = reinterpret_cast<unsigned short*>(smem_raw + SM_C2);
    uint2* soh = reinterpret_cast<uint2*>(smem_raw + SM_OH);
    __shared__ int cnts[NB + 32];
    __shared__ int gstart[NGRP + 1];
    __shared__ int warp_sums[NB / 32];

    const int tid = threadIdx.x;
    const int lane = tid & 31, wid = tid >> 5;
    const int bin = blockIdx.x;
    if (bin < p.nsm * G_BLOCKS) {
        const int slot = (bin / p.nsm + bin) % G_BLOCKS;
        for (int k = 0; k < slot * (CFG_STAGGER_NS / 500); k++) __nanosleep(500);
    }
    const int total = g_cursor[bin];
    bool ovf = total > CAPG;
    const int n = ovf ? 0 : total;

    const uint4* rec = reinterpret_cast<const uint4*>(g_records + (size_t)bin * CAPG) + tid;
    uint4 r[G_PER / 2];
#pragma unroll
    for (int j = 0; j < G_PER / 2; j++) {
        r[j] = make_uint4(0u, 0xffffffffu, 0u, 0xffffffffu);
        if ((j * G_NT + tid) * 2 < n) r[j] = __ldcs(rec + j * G_NT);
    }
    if (tid < NB) cnts[tid] = 0;
    for (int i = tid; i < (G_NT / 32) * G_STAGES * 64; i += G_NT)
        reinterpret_cast<uint4*>(smem_raw + SM_RING)[i] = make_uint4(0u, 0u, 0u, 0u);
    const unsigned short* fq = reinterpret_cast<const unsigned short*>(p.ang_freq);
    const uint32_t f0 = (uint32_t)fq[0] * 0x10001u, f1 = (uint32_t)fq[1] * 0x10001u, f2 = (uint32_t)fq[2] * 0x10001u;
    const uint32_t fmaxp = max(max(f0 & 0x7fff7fffu, f1 & 0x7fff7fffu), f2 & 0x7fff7fffu);
    const uint32_t dkey = NB + lane;
    __syncthreads();
    if (tid == 0) g_cursor[bin] = 0;
#pragma unroll
    for (int j = 0; j < G_PER / 2; j++) {
        atomicAdd(&cnts[min(r[j].y >> 16, dkey)], 1);
        atomicAdd(&cnts[min(r[j].w >> 16, dkey)], 1);
    }
    __syncthreads();
    int c = 0, inc = 0, cp = 0, npad = 0;
    if (tid < NB) {
        c = cnts[tid];
        int gt = c;
        gt += __shfl_xor_sync(0xffffffffu, gt, 1);
        gt += __shfl_xor_sync(0xffffffffu, gt, 2);
        gt += __shfl_xor_sync(0xffffffffu, gt, 4);
        npad = ((gt + 31) & ~31) - gt;
        cp = c + (((lane & 7) == 7) ? npad : 0);
        inc = cp;
#pragma unroll
        for (int o = 1; o < 32; o <<= 1) {
            int t = __shfl_up_sync(0xffffffffu, inc, o);
            if (lane >= o) inc += t;
        }
        if (lane == 31) warp_sums[wid] = inc;
    }
    __syncthreads();
    {
        int woff = 0, tot = 0;
#pragma unroll
        for (int w = 0; w < NB / 32; w++) { woff += (w < wid) ? warp_sums[w] : 0; tot += warp_sums[w]; }
        ovf = ovf || (tot > CAPS);
        if (tid < NB) {
            const int st = ovf ? 0 : woff + inc - cp;
            cnts[tid] = ovf ? CAPS : st;
            if ((lane & 7) == 0) gstart[tid >> 3] = st;
            if (tid == NB - 1) gstart[NGRP] = ovf ? 0 : tot;
            if (tid < 32) cnts[NB + tid] = CAPS;
            const int gend = __shfl_sync(0xffffffffu, woff + inc, lane | 7);
            if (!ovf) {
#pragma unroll
                for (int k = 0; k < 4; k++) {
                    const int kk = (lane & 7) + 8 * k;
                    if (kk < npad) { sidx[gend - 1 - kk] = 0u; sang[gend - 1 - kk] = 0; }
                }
            }
        }
    }
    __syncthreads();
#pragma unroll
    for (int j = 0; j < G_PER / 2; j++) {
        {
            const int pos = min(atomicAdd(&cnts[min(r[j].y >> 16, dkey)], 1), CAPS);
            sidx[pos] = r[j].x;
            sang[pos] = (unsigned short)r[j].y;
        }
        {
            const int pos = min(atomicAdd(&cnts[min(r[j].w >> 16, dkey)], 1), CAPS);
            sidx[pos] = r[j].z;
            sang[pos] = (unsigned short)r[j].w;
        }
    }
    if (ovf) slow_bin(&p, bin);
    {
        const int nb = bin + p.nsm * G_BLOCKS;
        if (tid < 8 && nb < p.nbins) {
            const int cnt = min(g_cursor[nb], CAPG);
            const int per = ((cnt + 31) >> 5) << 2;
            const int lo = tid * per, len = min(per, cnt - lo);
            if (len > 0)
                asm volatile("cp.async.bulk.prefetch.L2.global [%0], %1;" :: "l"(g_records + (size_t)nb * CAPG + lo), "r"(len * 8) : "memory");
        }
    }
    __syncthreads();

    const int g = lane >> 2, q = lane & 3;
    constexpr int GPW = NGRP / (G_NT / 32);
    const int grp0 = wid * GPW;
    const int wbeg = gstart[grp0], wend = gstart[grp0 + GPW];
    const unsigned char* mb = reinterpret_cast<const unsigned char*>(p.m);
    const uint32_t sbase = smem_u32(smem_raw);

    const uint32_t ring = sbase + SM_RING + wid * (G_STAGES * 1024);
    const int cj = lane >> 1;
    const int crow = (cj >> 2) * 2 + (cj & 1) + ((cj >> 1) & 1) * 8;
    const uint32_t cdst = ring + (uint32_t)(crow * 32 + (((lane ^ (crow >> 2)) & 1) * 16));
    const unsigned char* msrc = mb + (lane & 1) * 16;
    const int lrow = (lane >> 4) * 8 + (lane & 7);
    const uint32_t lsrc = ring + (uint32_t)(lrow * 32 + ((((lane >> 3) ^ (lrow >> 2)) & 1) * 16));

    uint32_t iaddr = sbase + SM_IDX + (wbeg + 2 * cj) * 4;
    const uint32_t iend = sbase + SM_IDX + wend * 4;
    uint32_t ioff = 0;
#pragma unroll
    for (int k = 0; k < G_STAGES - 1; k++) {
        if (iaddr < iend) {
            const uint2 w = lds64(iaddr);
            cp_async_row(cdst + ioff, msrc, w.x);
            cp_async_row(cdst + ioff + 512, msrc, w.y);
        }
        cp_async_commit();
        iaddr += 128; ioff += 1024;
    }

    {
        const int noct = gstart[NGRP] >> 3;
        for (int i = tid; i < noct; i += G_NT) {
            const uint4 an = reinterpret_cast<const uint4*>(sang)[i];
            const uint4 w0 = reinterpret_cast<const uint4*>(sidx)[2 * i];
            const uint4 w1 = reinterpret_cast<const uint4*>(sidx)[2 * i + 1];
            soh[i] = make_uint2(prmt(prmt(w0.x, w0.z, 0x0073), prmt(w1.x, w1.z, 0x0073), 0x5410),
                                prmt(prmt(w0.y, w0.w, 0x0073), prmt(w1.y, w1.w, 0x0073), 0x5410));
            const uint32_t aA0 = prmt(an.x, an.y, 0x5410), aA1 = prmt(an.z, an.w, 0x5410);
            const uint32_t aB0 = prmt(an.x, an.y, 0x7632), aB1 = prmt(an.z, an.w, 0x7632);
            const uint32_t amax = __vmaxu2(__vmaxu2(an.x & 0x7fff7fffu, an.y & 0x7fff7fffu), __vmaxu2(an.z & 0x7fff7fffu, an.w & 0x7fff7fffu));
            const uint32_t t = mul_bf16x2(amax, fmaxp);
            uint4 oA, oB, o2;
            if ((t >> 16) < 0x4300u && (t & 0xffffu) < 0x4300u) {
                oA.x = cos_fast_bf16x2(mul_bf16x2(aA0, f0)); oA.y = cos_fast_bf16x2(mul_bf16x2(aA1, f0));
                oA.z = cos_fast_bf16x2(mul_bf16x2(aA0, f1)); oA.w = cos_fast_bf16x2(mul_bf16x2(aA1, f1));
                oB.x = cos_fast_bf16x2(mul_bf16x2(aB0, f0)); oB.y = cos_fast_bf16x2(mul_bf16x2(aB1, f0));
                oB.z = cos_fast_bf16x2(mul_bf16x2(aB0, f1)); oB.w = cos_fast_bf16x2(mul_bf16x2(aB1, f1));
                o2.x = cos_fast_bf16x2(mul_bf16x2(aA0, f2)); o2.y = cos_fast_bf16x2(mul_bf16x2(aA1, f2));
                o2.z = cos_fast_bf16x2(mul_bf16x2(aB0, f2)); o2.w = cos_fast_bf16x2(mul_bf16x2(aB1, f2));
            } else {
                oA.x = cos_slow_bf16x2(mul_bf16x2(aA0, f0)); oA.y = cos_slow_bf16x2(mul_bf16x2(aA1, f0));
                oA.z = cos_slow_bf16x2(mul_bf16x2(aA0, f1)); oA.w = cos_slow_bf16x2(mul_bf16x2(aA1, f1));
                oB.x = cos_slow_bf16x2(mul_bf16x2(aB0, f0)); oB.y = cos_slow_bf16x2(mul_bf16x2(aB1, f0));
                oB.z = cos_slow_bf16x2(mul_bf16x2(aB0, f1)); oB.w = cos_slow_bf16x2(mul_bf16x2(aB1, f1));
                o2.x = cos_slow_bf16x2(mul_bf16x2(aA0, f2)); o2.y = cos_slow_bf16x2(mul_bf16x2(aA1, f2));
                o2.z = cos_slow_bf16x2(mul_bf16x2(aB0, f2)); o2.w = cos_slow_bf16x2(mul_bf16x2(aB1, f2));
            }
            scA[i] = oA;
            scB[i] = oB;
            reinterpret_cast<uint4*>(sang)[i] = o2;
        }
    }

    uint32_t adown[4], aup[4], asbf[NL][2], arb[2];
    {
        const uint4* fr = reinterpret_cast<const uint4*>(g_frag) + lane;
        const uint4 t0 = __ldg(fr), t1 = __ldg(fr + 32), t2 = __ldg(fr + 64), t3 = __ldg(fr + 96);
        adown[0] = t0.x; adown[1] = t0.y; adown[2] = t0.z; adown[3] = t0.w;
        aup[0] = t1.x; aup[1] = t1.y; aup[2] = t1.z; aup[3] = t1.w;
        asbf[0][0] = t2.x; asbf[0][1] = t2.y; asbf[1][0] = t2.z; asbf[1][1] = t2.w;
        asbf[2][0] = t3.x; asbf[2][1] = t3.y; arb[0] = t3.z; arb[1] = t3.w;
    }
    const uint32_t cen = reinterpret_cast<const uint32_t*>(p.centers)[q];

    const int ew = bin * NB + grp0 * 8;
    const unsigned short* pdist = reinterpret_cast<const unsigned short*>(p.dist) + ew + g;
    const uint32_t moff0 = (uint32_t)(ew + 2 * q) * 32u + 4u * g;
    const int nleft = p.E - ew;
    uint32_t dgn = (g < nleft) ? (uint32_t)pdist[0] : 0u;
    uint32_t man = (2 * q < nleft) ? __ldg(reinterpret_cast<const uint32_t*>(mb + moff0)) : 0u;
    uint32_t mbn = (2 * q + 1 < nleft) ? __ldg(reinterpret_cast<const uint32_t*>(mb + moff0 + 32)) : 0u;
    __syncthreads();

    uint2 wnext = make_uint2(0u, 0u);
    if (iaddr < iend) wnext = lds64(iaddr);
    uint32_t ac = sbase + SM_CA + ((wbeg >> 3) + q) * 16;
    uint32_t aoh = sbase + SM_OH + ((wbeg >> 3) + q) * 8;
    uint2 ohnext = lds64(aoh);
    uint4 cA = make_uint4(0u, 0u, 0u, 0u), cB = cA, c2 = cA;
#pragma unroll 1
    for (int gi = 0; gi < GPW; gi++) {
        const uint32_t aend = sbase + SM_OH + (uint32_t)gstart[grp0 + gi + 1];
        const uint32_t moff = moff0 + gi * 256;
        const bool va = gi * 8 + 2 * q < nleft, vb = gi * 8 + 2 * q + 1 < nleft;
        const uint32_t dg = dgn, ma = man, mbv = mbn;
        if (gi + 1 < GPW) {
            dgn = (gi * 8 + 8 + g < nleft) ? (uint32_t)pdist[gi * 8 + 8] : 0u;
            man = (gi * 8 + 8 + 2 * q < nleft) ? __ldg(reinterpret_cast<const uint32_t*>(mb + moff + 256)) : 0u;
            mbn = (gi * 8 + 9 + 2 * q < nleft) ? __ldg(reinterpret_cast<const uint32_t*>(mb + moff + 288)) : 0u;
        }

        float D[NL][4];
#pragma unroll
        for (int l = 0; l < NL; l++)
#pragma unroll
            for (int c4 = 0; c4 < 4; c4++) D[l][c4] = 0.f;
#pragma unroll 1
        while (aoh < aend) {
            cp_async_row(cdst + ioff, msrc, wnext.x);
            cp_async_row(cdst + ioff + 512, msrc, wnext.y);
            cp_async_commit();
            iaddr += 128; ioff = (ioff == (G_STAGES - 1) * 1024) ? 0 : ioff + 1024;
            wnext = make_uint2(0u, 0u);
            if (iaddr < iend) wnext = lds64(iaddr);
            const uint32_t kA = (ohnext.x >> g) & 0x01010101u, kB = (ohnext.y >> g) & 0x01010101u;
            asm volatile("{ .reg .pred pa, pb, pc; setp.ne.u32 pa, %13, 0; setp.ne.u32 pb, %14, 0; or.pred pc, pa, pb;\n\t"
                         "@pa ld.shared.v4.u32 {%0,%1,%2,%3}, [%12];\n\t"
                         "@pb ld.shared.v4.u32 {%4,%5,%6,%7}, [%12+%15];\n\t"
                         "@pc ld.shared.v4.u32 {%8,%9,%10,%11}, [%12+%16]; }"
                         : "+r"(cA.x), "+r"(cA.y), "+r"(cA.z), "+r"(cA.w), "+r"(cB.x), "+r"(cB.y), "+r"(cB.z), "+r"(cB.w),
                           "+r"(c2.x), "+r"(c2.y), "+r"(c2.z), "+r"(c2.w)
                         : "r"(ac), "r"(kA), "r"(kB), "n"(SM_CB - SM_CA), "n"(SM_C2 - SM_CA) : "memory");
            ac += 64; aoh += 32;
            ohnext = lds64(aoh);
            const uint32_t kA0 = prmt(kA, 0, 0x4140) * 0x3F80u, kA1 = prmt(kA, 0, 0x4342) * 0x3F80u;
            const uint32_t kB0 = prmt(kB, 0, 0x4140) * 0x3F80u, kB1 = prmt(kB, 0, 0x4342) * 0x3F80u;
            cp_async_wait<G_STAGES - 1>();
            __syncwarp();
            uint32_t a[4], b[4];
            ldsm_x4_trans(a, lsrc + ioff);
            ldsm_x4_trans(b, lsrc + ioff + 512);
            mma16816(D[0], a, mul_bf16x2(cA.x, kA0), mul_bf16x2(cA.y, kA1));
            mma16816(D[1], a, mul_bf16x2(cA.z, kA0), mul_bf16x2(cA.w, kA1));
            mma16816(D[2], a, mul_bf16x2(c2.x, kA0), mul_bf16x2(c2.y, kA1));
            mma16816(D[0], b, mul_bf16x2(cB.x, kB0), mul_bf16x2(cB.y, kB1));
            mma16816(D[1], b, mul_bf16x2(cB.z, kB0), mul_bf16x2(cB.w, kB1));
            mma16816(D[2], b, mul_bf16x2(c2.z, kB0), mul_bf16x2(c2.w, kB1));
        }
        const uint32_t brbf = rbf_bf16x2(dg * 0x10001u, cen);
        float agg[4] = {0.f, 0.f, 0.f, 0.f};
#pragma unroll
        for (int l = 0; l < NL; l++) {
            const uint32_t h0 = movm(pack_bf16(D[l][0], D[l][1]));
            const uint32_t h1 = movm(pack_bf16(D[l][2], D[l][3]));
            float S[4] = {0.f, 0.f, 0.f, 0.f};
            float G[4] = {0.f, 0.f, 0.f, 0.f};
            mma16816(S, adown, h0, h1);
            mma1688(G, asbf[l], brbf);
#pragma unroll
            for (int c4 = 0; c4 < 4; c4++) agg[c4] = fmaf(S[c4], G[c4], agg[c4]);
        }
        if (ovf) {
            const int ea = ew + gi * 8 + 2 * q;
            if (va) {
                float* pa = g_ovf + (size_t)ea * DE + g;
                agg[0] += __ldcg(pa); agg[2] += __ldcg(pa + 8);
                pa[0] = 0.f; pa[8] = 0.f;
            }
            if (vb) {
                float* pb = g_ovf + (size_t)(ea + 1) * DE + g;
                agg[1] += __ldcg(pb); agg[3] += __ldcg(pb + 8);
                pb[0] = 0.f; pb[8] = 0.f;
            }
        }
        {
            const uint32_t h0 = movm(pack_bf16(agg[0], agg[1]));
            const uint32_t h1 = movm(pack_bf16(agg[2], agg[3]));
            float U[4] = {0.f, 0.f, 0.f, 0.f};
            float R[4] = {0.f, 0.f, 0.f, 0.f};
            mma16816(U, aup, h0, h1);
            mma1688(R, arb, brbf);
            uint32_t oa = pack_bf16(fmaf(U[0], R[0], bf16lo(ma)), fmaf(U[2], R[2], bf16hi(ma)));
            uint32_t ob = pack_bf16(fmaf(U[1], R[1], bf16lo(mbv)), fmaf(U[3], R[3], bf16hi(mbv)));
            unsigned char* ob8 = reinterpret_cast<unsigned char*>(p.out);
            if (va) *reinterpret_cast<uint32_t*>(ob8 + moff) = oa;
            if (vb) *reinterpret_cast<uint32_t*>(ob8 + moff + 32) = ob;
        }
    }
}

}

extern "C" void kernel_launch(void* const* d_in, const int* in_sizes, int n_in,
                              void* d_out, int out_size) {
    Params p;
    p.m = (const __nv_bfloat16*)d_in[0];
    p.idx_in = (const int*)d_in[1];
    p.idx_out = (const int*)d_in[2];
    p.dist = (const __nv_bfloat16*)d_in[3];
    p.angle = (const __nv_bfloat16*)d_in[4];
    p.centers = (const __nv_bfloat16*)d_in[5];
    p.ang_freq = (const __nv_bfloat16*)d_in[6];
    p.w_rbf = (const __nv_bfloat16*)d_in[7];
    p.w_sbf = (const __nv_bfloat16*)d_in[8];
    p.w_down = (const __nv_bfloat16*)d_in[9];
    p.w_up = (const __nv_bfloat16*)d_in[10];
    p.out = (__nv_bfloat16*)d_out;
    p.E = in_sizes[3];
    p.T = in_sizes[1];
    p.nbins = (p.E + NB - 1) / NB;

    const int smem1 = P_STAGE * 8 + (BINS_PAD + 4) * 4;
    const int smem2 = SM_TOTAL;
    static int nsm = 0;
    if (!nsm) {
        cudaFuncSetAttribute(k_partition, cudaFuncAttributeMaxDynamicSharedMemorySize, smem1);
        cudaFuncSetAttribute(k_gather, cudaFuncAttributeMaxDynamicSharedMemorySize, smem2);
        int dev = 0;
        cudaGetDevice(&dev);
        cudaDeviceGetAttribute(&nsm, cudaDevAttrMultiProcessorCount, dev);
    }
    p.nsm = nsm;
    long long per_sm = ((long long)p.T + nsm - 1) / nsm;
    int k = (int)((per_sm + P_TILE_MAX - 1) / P_TILE_MAX);
    if (k < 1) k = 1;
    long long tile = ((long long)p.T + (long long)k * nsm - 1) / ((long long)k * nsm);
    tile = (tile + 15) & ~15LL;
    if (tile > P_TILE_MAX) tile = P_TILE_MAX;
    if (tile < 16) tile = 16;
    p.tile = (int)tile;
    p.ntiles = (int)(((long long)p.T + tile - 1) / tile);
    int g1 = p.ntiles < nsm ? p.ntiles : nsm;
    if (g1 < 1) g1 = 1;
    k_partition<<<g1, P_NT, smem1>>>(p);
    k_gather<<<p.nbins, G_NT, smem2>>>(p);
}
```

```cpp
#include <cuda_runtime.h>
#include <cuda_bf16.h>
#include <stdint.h>

namespace {

constexpr int DE = 16;
constexpr int NR = 8;
constexpr int NL = 3;

constexpr int NB_LOG = 8;
constexpr int NB = 1 << NB_LOG;
constexpr int MAX_E = 400000;
constexpr int MAX_BINS = (MAX_E + NB - 1) / NB;
constexpr int BINS_PAD = 2048;
constexpr int CAPG = 5120;

constexpr int P_NT = 1024;
constexpr int P_PER = 16;
constexpr int P_TILE_MAX = P_NT * P_PER;
constexpr int P_STAGE = P_TILE_MAX + 3 * MAX_BINS + 16;

#define CFG_G_NT 256
#define CFG_G_BLOCKS 3
#define CFG_G_STAGES 2
#define CFG_STAGGER_NS 0
#define CFG_PREFETCH 0
constexpr int G_NT = CFG_G_NT;
constexpr int G_BLOCKS = CFG_G_BLOCKS;
constexpr int G_PER = CAPG / G_NT;
constexpr int NGRP = NB / 8;
constexpr int CAPS = 5120;
constexpr int G_STAGES = CFG_G_STAGES;

__device__ uint2 g_records[(size_t)MAX_BINS * CAPG];
__device__ int g_cursor[BINS_PAD];
__device__ uint4 g_frag[4 * 32];
__device__ float g_ovf[(size_t)MAX_BINS * NB * DE];

__device__ __forceinline__ float bf16r(float x) { return __bfloat162float(__float2bfloat16_rn(x)); }
__device__ __forceinline__ float bf16lo(uint32_t v) { return __uint_as_float(v << 16); }
__device__ __forceinline__ float bf16hi(uint32_t v) { return __uint_as_float(v & 0xffff0000u); }
__device__ __forceinline__ float ldbf(const __nv_bfloat16* p) { return __bfloat162float(*p); }
__device__ __forceinline__ uint32_t smem_u32(const void* p) { return (uint32_t)__cvta_generic_to_shared(p); }

__device__ __forceinline__ uint32_t pack_bf16(float lo, float hi) {
    __nv_bfloat162 v = __floats2bfloat162_rn(lo, hi);
    return *reinterpret_cast<uint32_t*>(&v);
}
__device__ __forceinline__ uint32_t mul_bf16x2(uint32_t a, uint32_t b) {
    __nv_bfloat162 r = __hmul2(*reinterpret_cast<__nv_bfloat162*>(&a), *reinterpret_cast<__nv_bfloat162*>(&b));
    return *reinterpret_cast<uint32_t*>(&r);
}
__device__ __forceinline__ uint32_t sub_bf16x2(uint32_t a, uint32_t b) {
    __nv_bfloat162 r = __hsub2(*reinterpret_cast<__nv_bfloat162*>(&a), *reinterpret_cast<__nv_bfloat162*>(&b));
    return *reinterpret_cast<uint32_t*>(&r);
}
__device__ __forceinline__ uint32_t cos_fast_bf16x2(uint32_t x) {
    return pack_bf16(__cosf(bf16lo(x)), __cosf(bf16hi(x)));
}
__device__ __noinline__ uint32_t cos_slow_bf16x2(uint32_t x) {
    return pack_bf16(cosf(bf16lo(x)), cosf(bf16hi(x)));
}
__device__ __forceinline__ uint32_t rbf_bf16x2(uint32_t dd, uint32_t cc) {
    uint32_t t = sub_bf16x2(dd, cc);
    t = mul_bf16x2(t, t);
    t = mul_bf16x2(t, 0xC120C120u);
    return pack_bf16(__expf(bf16lo(t)), __expf(bf16hi(t)));
}

__device__ __forceinline__ void mma16816(float* d, const uint32_t* a, uint32_t b0, uint32_t b1) {
    asm volatile("mma.sync.aligned.m16n8k16.row.col.f32.bf16.bf16.f32 {%0,%1,%2,%3}, {%4,%5,%6,%7}, {%8,%9}, {%0,%1,%2,%3};"
                 : "+f"(d[0]), "+f"(d[1]), "+f"(d[2]), "+f"(d[3])
                 : "r"(a[0]), "r"(a[1]), "r"(a[2]), "r"(a[3]), "r"(b0), "r"(b1));
}
__device__ __forceinline__ void mma1688(float* d, const uint32_t* a, uint32_t b) {
    asm volatile("mma.sync.aligned.m16n8k8.row.col.f32.bf16.bf16.f32 {%0,%1,%2,%3}, {%4,%5}, {%6}, {%0,%1,%2,%3};"
                 : "+f"(d[0]), "+f"(d[1]), "+f"(d[2]), "+f"(d[3])
                 : "r"(a[0]), "r"(a[1]), "r"(b));
}
__device__ __forceinline__ uint32_t movm(uint32_t a) {
    uint32_t d;
    asm volatile("movmatrix.sync.aligned.m8n8.trans.b16 %0, %1;" : "=r"(d) : "r"(a));
    return d;
}
__device__ __forceinline__ uint32_t prmt(uint32_t a, uint32_t b, uint32_t sel) {
    uint32_t d;
    asm("prmt.b32 %0, %1, %2, %3;" : "=r"(d) : "r"(a), "r"(b), "r"(sel));
    return d;
}
__device__ __forceinline__ void ldsm_x4_trans(uint32_t* r, uint32_t addr) {
    asm volatile("ldmatrix.sync.aligned.m8n8.x4.trans.shared.b16 {%0,%1,%2,%3}, [%4];"
                 : "=r"(r[0]), "=r"(r[1]), "=r"(r[2]), "=r"(r[3]) : "r"(addr) : "memory");
}
__device__ __forceinline__ void cp_async_row(uint32_t dst, const unsigned char* base, uint32_t w) {
    uint64_t addr;
    asm("mad.wide.u32 %0, %1, 1, %2;" : "=l"(addr) : "r"(w & 0xffffffu), "l"(base));
    asm volatile("{ .reg .pred p; setp.gt.u32 p, %2, 0xffffff; @p cp.async.cg.shared.global [%0], [%1], 16; }" :: "r"(dst), "l"(addr), "r"(w) : "memory");
}
__device__ __forceinline__ void cp_async_commit() { asm volatile("cp.async.commit_group;" ::: "memory"); }
template <int N> __device__ __forceinline__ void cp_async_wait() { asm volatile("cp.async.wait_group %0;" :: "n"(N) : "memory"); }

struct Params {
    const __nv_bfloat16* m;
    const int* idx_in;
    const int* idx_out;
    const __nv_bfloat16* dist;
    const __nv_bfloat16* angle;
    const __nv_bfloat16* centers;
    const __nv_bfloat16* ang_freq;
    const __nv_bfloat16* w_rbf;
    const __nv_bfloat16* w_sbf;
    const __nv_bfloat16* w_down;
    const __nv_bfloat16* w_up;
    __nv_bfloat16* out;
    int E, T, nbins, ntiles, tile, nsm;
};

__device__ __noinline__ void slow_bin(const Params* pp, int bin) {
    const Params& p = *pp;
    for (int t = threadIdx.x; t < p.T; t += blockDim.x) {
        const int out = p.idx_out[t];
        if ((out >> NB_LOG) != bin) continue;
        const int in = p.idx_in[t];
        const float ang = ldbf(p.angle + t);
        float mrow[DE], rb[NR], cb[NL];
        for (int k = 0; k < DE; k++) mrow[k] = ldbf(p.m + (size_t)in * DE + k);
        float d = ldbf(p.dist + out);
        for (int r = 0; r < NR; r++) {
            float u = bf16r(d - ldbf(p.centers + r));
            u = bf16r(u * u);
            u = bf16r(-10.0f * u);
            rb[r] = bf16r(__expf(u));
        }
        for (int l = 0; l < NL; l++) cb[l] = bf16r(cosf(bf16r(ldbf(p.ang_freq + l) * ang)));
        for (int c = 0; c < DE; c++) {
            float md = 0.f, s = 0.f;
            for (int k = 0; k < DE; k++) md = fmaf(mrow[k], ldbf(p.w_down + k * DE + c), md);
            for (int r = 0; r < NR; r++)
                for (int l = 0; l < NL; l++) s = fmaf(rb[r] * cb[l], ldbf(p.w_sbf + (r * NL + l) * DE + c), s);
            atomicAdd(&g_ovf[(size_t)out * DE + c], md * s);
        }
    }
    __threadfence();
}

__device__ __forceinline__ int4 ld4_guard(const int* p, int i, int n, int fill) {
    if (i + 3 < n) return __ldcs(reinterpret_cast<const int4*>(p + i));
    int4 r;
    r.x = (i + 0 < n) ? p[i + 0] : fill;
    r.y = (i + 1 < n) ? p[i + 1] : fill;
    r.z = (i + 2 < n) ? p[i + 2] : fill;
    r.w = fill;
    return r;
}
__device__ __forceinline__ uint2 ld4h_guard(const unsigned short* p, int i, int n) {
    if (i + 3 < n) return __ldcs(reinterpret_cast<const uint2*>(p + i));
    uint32_t a = (i + 0 < n) ? p[i + 0] : 0u, b = (i + 1 < n) ? p[i + 1] : 0u, c = (i + 2 < n) ? p[i + 2] : 0u;
    return make_uint2(a | (b << 16), c);
}

__global__ void __launch_bounds__(P_NT, 1) k_partition(const __grid_constant__ Params p) {
    extern __shared__ __align__(16) unsigned char smem_raw[];
    uint2* stage = reinterpret_cast<uint2*>(smem_raw);
    int* hist = reinterpret_cast<int*>(smem_raw + (size_t)P_STAGE * 8);
    __shared__ int warp_sums[P_NT / 32];
    static_assert(BINS_PAD == 2 * P_NT, "two bins per thread in the scan");

    const int tid = threadIdx.x;
    const int lane = tid & 31, wid = tid >> 5;
    const unsigned short* ang16 = reinterpret_cast<const unsigned short*>(p.angle);

    if (blockIdx.x == 0 && wid == P_NT / 32 - 1) {
        const int g = lane >> 2, q = lane & 3;
        const unsigned short* wd = reinterpret_cast<const unsigned short*>(p.w_down);
        const unsigned short* wu = reinterpret_cast<const unsigned short*>(p.w_up);
        const unsigned short* ws = reinterpret_cast<const unsigned short*>(p.w_sbf);
        const unsigned short* wr = reinterpret_cast<const unsigned short*>(p.w_rbf);
        uint4 t;
        t.x = (uint32_t)wd[(2 * q) * DE + g] | ((uint32_t)wd[(2 * q + 1) * DE + g] << 16);
        t.y = (uint32_t)wd[(2 * q) * DE + g + 8] | ((uint32_t)wd[(2 * q + 1) * DE + g + 8] << 16);
        t.z = (uint32_t)wd[(2 * q + 8) * DE + g] | ((uint32_t)wd[(2 * q + 9) * DE + g] << 16);
        t.w = (uint32_t)wd[(2 * q + 8) * DE + g + 8] | ((uint32_t)wd[(2 * q + 9) * DE + g + 8] << 16);
        g_frag[lane] = t;
        const int cA = 2 * g, cB = 2 * g + 1;
        t.x = (uint32_t)wu[(2 * q) * DE + cA] | ((uint32_t)wu[(2 * q + 1) * DE + cA] << 16);
        t.y = (uint32_t)wu[(2 * q) * DE + cB] | ((uint32_t)wu[(2 * q + 1) * DE + cB] << 16);
        t.z = (uint32_t)wu[(2 * q + 8) * DE + cA] | ((uint32_t)wu[(2 * q + 9) * DE + cA] << 16);
        t.w = (uint32_t)wu[(2 * q + 8) * DE + cB] | ((uint32_t)wu[(2 * q + 9) * DE + cB] << 16);
        g_frag[32 + lane] = t;
        uint32_t sb[NL][2];
#pragma unroll
        for (int l = 0; l < NL; l++) {
            sb[l][0] = (uint32_t)ws[((2 * q) * NL + l) * DE + g] | ((uint32_t)ws[((2 * q + 1) * NL + l) * DE + g] << 16);
            sb[l][1] = (uint32_t)ws[((2 * q) * NL + l) * DE + g + 8] | ((uint32_t)ws[((2 * q + 1) * NL + l) * DE + g + 8] << 16);
        }
        g_frag[64 + lane] = make_uint4(sb[0][0], sb[0][1], sb[1][0], sb[1][1]);
        t.x = sb[2][0]; t.y = sb[2][1];
        t.z = (uint32_t)wr[(2 * q) * DE + cA] | ((uint32_t)wr[(2 * q + 1) * DE + cA] << 16);
        t.w = (uint32_t)wr[(2 * q) * DE + cB] | ((uint32_t)wr[(2 * q + 1) * DE + cB] << 16);
        g_frag[96 + lane] = t;
    }

    int4 O[P_PER / 4];
    int tile = blockIdx.x;
    if (tile < p.ntiles) {
        const int base = tile * p.tile, n = min(p.tile, p.T - base);
#pragma unroll
        for (int v = 0; v < P_PER / 4; v++) O[v] = ld4_guard(p.idx_out + base, (v * P_NT + tid) * 4, n, -1);
    }
    reinterpret_cast<int2*>(hist)[tid] = make_int2(0, 0);
    if (tid == 0) hist[BINS_PAD] = 0;
    for (; tile < p.ntiles; tile += gridDim.x) {
        const int base = tile * p.tile, n = min(p.tile, p.T - base);
        __syncthreads();
#pragma unroll
        for (int v = 0; v < P_PER / 4; v++) {
            atomicAdd(&hist[min((uint32_t)O[v].x >> NB_LOG, (uint32_t)BINS_PAD)], 1);
            atomicAdd(&hist[min((uint32_t)O[v].y >> NB_LOG, (uint32_t)BINS_PAD)], 1);
            atomicAdd(&hist[min((uint32_t)O[v].z >> NB_LOG, (uint32_t)BINS_PAD)], 1);
            atomicAdd(&hist[min((uint32_t)O[v].w >> NB_LOG, (uint32_t)BINS_PAD)], 1);
        }
        int4 I[P_PER / 4];
        uint2 A[P_PER / 4];
#pragma unroll
        for (int v = 0; v < P_PER / 4; v++) {
            I[v] = ld4_guard(p.idx_in + base, (v * P_NT + tid) * 4, n, 0);
            A[v] = ld4h_guard(ang16 + base, (v * P_NT + tid) * 4, n);
        }
        __syncthreads();
        const int2 c2 = reinterpret_cast<int2*>(hist)[tid];
        const int pc0 = (c2.x + 3) & ~3, pc1 = (c2.y + 3) & ~3;
        int g0 = 0, g1 = 0;
        if (pc0) g0 = atomicAdd(&g_cursor[2 * tid], pc0);
        if (pc1) g1 = atomicAdd(&g_cursor[2 * tid + 1], pc1);
        const int s = pc0 + pc1;
        int inc = s;
#pragma unroll
        for (int o = 1; o < 32; o <<= 1) {
            int t = __shfl_up_sync(0xffffffffu, inc, o);
            if (lane >= o) inc += t;
        }
        if (lane == 31) warp_sums[wid] = inc;
        asm volatile("cp.async.bulk.wait_group.read 0;" ::: "memory");
        __syncthreads();
        int woff;
        {
            int ws = warp_sums[lane];
            int winc = ws;
#pragma unroll
            for (int o = 1; o < 32; o <<= 1) {
                int t = __shfl_up_sync(0xffffffffu, winc, o);
                if (lane >= o) winc += t;
            }
            woff = __shfl_sync(0xffffffffu, winc - ws, wid);
        }
        const int e0 = woff + inc - s, e1 = e0 + pc0;
        reinterpret_cast<int2*>(hist)[tid] = make_int2(e0, e1);
        if (tid == 0) hist[BINS_PAD] = P_STAGE;
        for (int k = c2.x; k < pc0; k++) stage[e0 + k] = make_uint2(0u, 0xffffffffu);
        for (int k = c2.y; k < pc1; k++) stage[e1 + k] = make_uint2(0u, 0xffffffffu);
        __syncthreads();
#pragma unroll
        for (int v = 0; v < P_PER / 4; v++) {
            const uint32_t o[4] = {(uint32_t)O[v].x, (uint32_t)O[v].y, (uint32_t)O[v].z, (uint32_t)O[v].w};
            const uint32_t in[4] = {(uint32_t)I[v].x, (uint32_t)I[v].y, (uint32_t)I[v].z, (uint32_t)I[v].w};
            const uint32_t an[4] = {A[v].x & 0xffffu, A[v].x >> 16, A[v].y & 0xffffu, A[v].y >> 16};
#pragma unroll
            for (int u = 0; u < 4; u++) {
                int pos = atomicAdd(&hist[min(o[u] >> NB_LOG, (uint32_t)BINS_PAD)], 1);
                stage[min(pos, P_STAGE - 1)] = make_uint2((in[u] << 5) | (0x1000000u << (o[u] & 7)), an[u] | ((o[u] & 255u) << 16));
            }
        }
        {
            const int nt = tile + gridDim.x;
            if (nt < p.ntiles) {
                const int nbase = nt * p.tile, nn = min(p.tile, p.T - nbase);
#pragma unroll
                for (int v = 0; v < P_PER / 4; v++) O[v] = ld4_guard(p.idx_out + nbase, (v * P_NT + tid) * 4, nn, -1);
            }
        }
        asm volatile("fence.proxy.async.shared::cta;" ::: "memory");
        __syncthreads();
        if (pc0 && g0 + pc0 <= CAPG)
            asm volatile("cp.async.bulk.global.shared::cta.bulk_group [%0], [%1], %2;"
                         :: "l"(g_records + (size_t)(2 * tid) * CAPG + g0), "r"(smem_u32(stage + e0)), "r"(pc0 * 8) : "memory");
        if (pc1 && g1 + pc1 <= CAPG)
            asm volatile("cp.async.bulk.global.shared::cta.bulk_group [%0], [%1], %2;"
                         :: "l"(g_records + (size_t)(2 * tid + 1) * CAPG + g1), "r"(smem_u32(stage + e1)), "r"(pc1 * 8) : "memory");
        asm volatile("cp.async.bulk.commit_group;" ::: "memory");
        reinterpret_cast<int2*>(hist)[tid] = make_int2(0, 0);
        if (tid == 0) hist[BINS_PAD] = 0;
    }
    asm volatile("cp.async.bulk.wait_group 0;" ::: "memory");
}

constexpr int NOCT = CAPS / 8;
constexpr int SM_IDX = 0;
constexpr int SM_CA = SM_IDX + (CAPS + 32) * 4;
constexpr int SM_CB = SM_CA + NOCT * 16;
constexpr int SM_C2 = SM_CB + NOCT * 16;
constexpr int SM_OH = SM_C2 + (NOCT + 4) * 16;
constexpr int SM_RING = SM_OH + (NOCT + 8) * 8;
constexpr int SM_TOTAL = SM_RING + (G_NT / 32) * G_STAGES * 1024;

__device__ __forceinline__ uint2 lds64(uint32_t a) { uint2 v; asm volatile("ld.shared.v2.u32 {%0,%1}, [%2];" : "=r"(v.x), "=r"(v.y) : "r"(a) : "memory"); return v; }

__global__ void __launch_bounds__(G_NT, G_BLOCKS) k_gather(const __grid_constant__ Params p) {
    extern __shared__ __align__(128) unsigned char smem_raw[];
    uint32_t* sidx = reinterpret_cast<uint32_t*>(smem_raw + SM_IDX);
    uint4* scA = reinterpret_cast<uint4*>(smem_raw + SM_CA);
    uint4* scB = reinterpret_cast<uint4*>(smem_raw + SM_CB);
    unsigned short* sang = reinterpret_cast<unsigned short*>(smem_raw + SM_C2);
    uint2* soh = reinterpret_cast<uint2*>(smem_raw + SM_OH);
    __shared__ int cnts[NB + 32];
    __shared__ int gstart[NGRP + 1];
    __shared__ int warp_sums[NB / 32];

    const int tid = threadIdx.x;
    const int lane = tid & 31, wid = tid >> 5;
    const int bin = blockIdx.x;
    const int total = g_cursor[bin];
    bool ovf = total > CAPG;
    const int n = ovf ? 0 : total;

    const uint4* rec = reinterpret_cast<const uint4*>(g_records + (size_t)bin * CAPG) + tid;
    uint4 r[G_PER / 2];
#pragma unroll
    for (int j = 0; j < G_PER / 2; j++) {
        r[j] = make_uint4(0u, 0xffffffffu, 0u, 0xffffffffu);
        if ((j * G_NT + tid) * 2 < n) r[j] = __ldcs(rec + j * G_NT);
    }
    if (tid < NB) cnts[tid] = 0;
    for (int i = tid; i < (G_NT / 32) * G_STAGES * 64; i += G_NT)
        reinterpret_cast<uint4*>(smem_raw + SM_RING)[i] = make_uint4(0u, 0u, 0u, 0u);
    const unsigned short* fq = reinterpret_cast<const unsigned short*>(p.ang_freq);
    const uint32_t f0 = (uint32_t)fq[0] * 0x10001u, f1 = (uint32_t)fq[1] * 0x10001u, f2 = (uint32_t)fq[2] * 0x10001u;
    const uint32_t fmaxp = max(max(f0 & 0x7fff7fffu, f1 & 0x7fff7fffu), f2 & 0x7fff7fffu);
    const uint32_t dkey = NB + lane;
    __syncthreads();
    if (tid == 0) g_cursor[bin] = 0;
#pragma unroll
    for (int j = 0; j < G_PER / 2; j++) {
        atomicAdd(&cnts[min(r[j].y >> 16, dkey)], 1);
        atomicAdd(&cnts[min(r[j].w >> 16, dkey)], 1);
    }
    __syncthreads();
    int c = 0, inc = 0, cp = 0, npad = 0;
    if (tid < NB) {
        c = cnts[tid];
        int gt = c;
        gt += __shfl_xor_sync(0xffffffffu, gt, 1);
        gt += __shfl_xor_sync(0xffffffffu, gt, 2);
        gt += __shfl_xor_sync(0xffffffffu, gt, 4);
        npad = ((gt + 31) & ~31) - gt;
        cp = c + (((lane & 7) == 7) ? npad : 0);
        inc = cp;
#pragma unroll
        for (int o = 1; o < 32; o <<= 1) {
            int t = __shfl_up_sync(0xffffffffu, inc, o);
            if (lane >= o) inc += t;
        }
        if (lane == 31) warp_sums[wid] = inc;
    }
    __syncthreads();
    {
        int woff = 0, tot = 0;
#pragma unroll
        for (int w = 0; w < NB / 32; w++) { woff += (w < wid) ? warp_sums[w] : 0; tot += warp_sums[w]; }
        ovf = ovf || (tot > CAPS);
        if (tid < NB) {
            const int st = ovf ? 0 : woff + inc - cp;
            cnts[tid] = ovf ? CAPS : st;
            if ((lane & 7) == 0) gstart[tid >> 3] = st;
            if (tid == NB - 1) gstart[NGRP] = ovf ? 0 : tot;
            if (tid < 32) cnts[NB + tid] = CAPS;
            const int gend = __shfl_sync(0xffffffffu, woff + inc, lane | 7);
            if (!ovf) {
#pragma unroll
                for (int k = 0; k < 4; k++) {
                    const int kk = (lane & 7) + 8 * k;
                    if (kk < npad) { sidx[gend - 1 - kk] = 0u; sang[gend - 1 - kk] = 0; }
                }
            }
        }
    }
    __syncthreads();
#pragma unroll
    for (int j = 0; j < G_PER / 2; j++) {
        {
            const int pos = min(atomicAdd(&cnts[min(r[j].y >> 16, dkey)], 1), CAPS);
            sidx[pos] = r[j].x;
            sang[pos] = (unsigned short)r[j].y;
        }
        {
            const int pos = min(atomicAdd(&cnts[min(r[j].w >> 16, dkey)], 1), CAPS);
            sidx[pos] = r[j].z;
            sang[pos] = (unsigned short)r[j].w;
        }
    }
    if (ovf) slow_bin(&p, bin);
    __syncthreads();

    const int g = lane >> 2, q = lane & 3;
    constexpr int GPW = NGRP / (G_NT / 32);
    const int grp0 = wid * GPW;
    const int wbeg = gstart[grp0], wend = gstart[grp0 + GPW];
    const unsigned char* mb = reinterpret_cast<const unsigned char*>(p.m);
    const uint32_t sbase = smem_u32(smem_raw);

    const uint32_t ring = sbase + SM_RING + wid * (G_STAGES * 1024);
    const int cj = lane >> 1;
    const int crow = (cj >> 2) * 2 + (cj & 1) + ((cj >> 1) & 1) * 8;
    const uint32_t cdst = ring + (uint32_t)(crow * 32 + (((lane ^ (crow >> 2)) & 1) * 16));
    const unsigned char* msrc = mb + (lane & 1) * 16;
    const int lrow = (lane >> 4) * 8 + (lane & 7);
    const uint32_t lsrc = ring + (uint32_t)(lrow * 32 + ((((lane >> 3) ^ (lrow >> 2)) & 1) * 16));

    uint32_t iaddr = sbase + SM_IDX + (wbeg + 2 * cj) * 4;
    const uint32_t iend = sbase + SM_IDX + wend * 4;
    uint32_t ioff = 0;
#pragma unroll
    for (int k = 0; k < G_STAGES - 1; k++) {
        if (iaddr < iend) {
            const uint2 w = lds64(iaddr);
            cp_async_row(cdst + ioff, msrc, w.x);
            cp_async_row(cdst + ioff + 512, msrc, w.y);
        }
        cp_async_commit();
        iaddr += 128; ioff += 1024;
    }

    {
        const int noct = gstart[NGRP] >> 3;
        for (int i = tid; i < noct; i += G_NT) {
            const uint4 an = reinterpret_cast<const uint4*>(sang)[i];
            const uint4 w0 = reinterpret_cast<const uint4*>(sidx)[2 * i];
            const uint4 w1 = reinterpret_cast<const uint4*>(sidx)[2 * i + 1];
            soh[i] = make_uint2(prmt(prmt(w0.x, w0.z, 0x0073), prmt(w1.x, w1.z, 0x0073), 0x5410),
                                prmt(prmt(w0.y, w0.w, 0x0073), prmt(w1.y, w1.w, 0x0073), 0x5410));
            const uint32_t aA0 = prmt(an.x, an.y, 0x5410), aA1 = prmt(an.z, an.w, 0x5410);
            const uint32_t aB0 = prmt(an.x, an.y, 0x7632), aB1 = prmt(an.z, an.w, 0x7632);
            const uint32_t amax = __vmaxu2(__vmaxu2(an.x & 0x7fff7fffu, an.y & 0x7fff7fffu), __vmaxu2(an.z & 0x7fff7fffu, an.w & 0x7fff7fffu));
            const uint32_t t = mul_bf16x2(amax, fmaxp);
            uint4 oA, oB, o2;
            if ((t >> 16) < 0x4300u && (t & 0xffffu) < 0x4300u) {
                oA.x = cos_fast_bf16x2(mul_bf16x2(aA0, f0)); oA.y = cos_fast_bf16x2(mul_bf16x2(aA1, f0));
                oA.z = cos_fast_bf16x2(mul_bf16x2(aA0, f1)); oA.w = cos_fast_bf16x2(mul_bf16x2(aA1, f1));
                oB.x = cos_fast_bf16x2(mul_bf16x2(aB0, f0)); oB.y = cos_fast_bf16x2(mul_bf16x2(aB1, f0));
                oB.z = cos_fast_bf16x2(mul_bf16x2(aB0, f1)); oB.w = cos_fast_bf16x2(mul_bf16x2(aB1, f1));
                o2.x = cos_fast_bf16x2(mul_bf16x2(aA0, f2)); o2.y = cos_fast_bf16x2(mul_bf16x2(aA1, f2));
                o2.z = cos_fast_bf16x2(mul_bf16x2(aB0, f2)); o2.w = cos_fast_bf16x2(mul_bf16x2(aB1, f2));
            } else {
                oA.x = cos_slow_bf16x2(mul_bf16x2(aA0, f0)); oA.y = cos_slow_bf16x2(mul_bf16x2(aA1, f0));
                oA.z = cos_slow_bf16x2(mul_bf16x2(aA0, f1)); oA.w = cos_slow_bf16x2(mul_bf16x2(aA1, f1));
                oB.x = cos_slow_bf16x2(mul_bf16x2(aB0, f0)); oB.y = cos_slow_bf16x2(mul_bf16x2(aB1, f0));
                oB.z = cos_slow_bf16x2(mul_bf16x2(aB0, f1)); oB.w = cos_slow_bf16x2(mul_bf16x2(aB1, f1));
                o2.x = cos_slow_bf16x2(mul_bf16x2(aA0, f2)); o2.y = cos_slow_bf16x2(mul_bf16x2(aA1, f2));
                o2.z = cos_slow_bf16x2(mul_bf16x2(aB0, f2)); o2.w = cos_slow_bf16x2(mul_bf16x2(aB1, f2));
            }
            scA[i] = oA;
            scB[i] = oB;
            reinterpret_cast<uint4*>(sang)[i] = o2;
        }
    }

    const uint32_t cen = reinterpret_cast<const uint32_t*>(p.centers)[q];

    const int ew = bin * NB + grp0 * 8;
    const unsigned short* pdist = reinterpret_cast<const unsigned short*>(p.dist) + ew + g;
    const uint32_t moff0 = (uint32_t)(ew + 2 * q) * 32u + 4u * g;
    const int nleft = p.E - ew;
    uint32_t dgn = (g < nleft) ? (uint32_t)pdist[0] : 0u;
    uint32_t man = (2 * q < nleft) ? __ldg(reinterpret_cast<const uint32_t*>(mb + moff0)) : 0u;
    uint32_t mbn = (2 * q + 1 < nleft) ? __ldg(reinterpret_cast<const uint32_t*>(mb + moff0 + 32)) : 0u;
    __syncthreads();

    uint2 wnext = make_uint2(0u, 0u);
    if (iaddr < iend) wnext = lds64(iaddr);
    uint32_t ac = sbase + SM_CA + ((wbeg >> 3) + q) * 16;
    uint32_t aoh = sbase + SM_OH + ((wbeg >> 3) + q) * 8;
    uint2 ohnext = lds64(aoh);
    uint4 cA = make_uint4(0u, 0u, 0u, 0u), cB = cA, c2 = cA;
#pragma unroll 1
    for (int gi = 0; gi < GPW; gi++) {
        const uint32_t aend = sbase + SM_OH + (uint32_t)gstart[grp0 + gi + 1];
        const uint32_t moff = moff0 + gi * 256;
        const bool va = gi * 8 + 2 * q < nleft, vb = gi * 8 + 2 * q + 1 < nleft;
        const uint32_t dg = dgn, ma = man, mbv = mbn;
        if (gi + 1 < GPW) {
            dgn = (gi * 8 + 8 + g < nleft) ? (uint32_t)pdist[gi * 8 + 8] : 0u;
            man = (gi * 8 + 8 + 2 * q < nleft) ? __ldg(reinterpret_cast<const uint32_t*>(mb + moff + 256)) : 0u;
            mbn = (gi * 8 + 9 + 2 * q < nleft) ? __ldg(reinterpret_cast<const uint32_t*>(mb + moff + 288)) : 0u;
        }

        float D[NL][4];
#pragma unroll
        for (int l = 0; l < NL; l++)
#pragma unroll
            for (int c4 = 0; c4 < 4; c4++) D[l][c4] = 0.f;
#pragma unroll 1
        while (aoh < aend) {
            cp_async_row(cdst + ioff, msrc, wnext.x);
            cp_async_row(cdst + ioff + 512, msrc, wnext.y);
            cp_async_commit();
            iaddr += 128; ioff = (ioff == (G_STAGES - 1) * 1024) ? 0 : ioff + 1024;
            wnext = make_uint2(0u, 0u);
            if (iaddr < iend) wnext = lds64(iaddr);
            const uint32_t kA = (ohnext.x >> g) & 0x01010101u, kB = (ohnext.y >> g) & 0x01010101u;
            asm volatile("{ .reg .pred pa, pb, pc; setp.ne.u32 pa, %13, 0; setp.ne.u32 pb, %14, 0; or.pred pc, pa, pb;\n\t"
                         "@pa ld.shared.v4.u32 {%0,%1,%2,%3}, [%12];\n\t"
                         "@pb ld.shared.v4.u32 {%4,%5,%6,%7}, [%12+%15];\n\t"
                         "@pc ld.shared.v4.u32 {%8,%9,%10,%11}, [%12+%16]; }"
                         : "+r"(cA.x), "+r"(cA.y), "+r"(cA.z), "+r"(cA.w), "+r"(cB.x), "+r"(cB.y), "+r"(cB.z), "+r"(cB.w),
                           "+r"(c2.x), "+r"(c2.y), "+r"(c2.z), "+r"(c2.w)
                         : "r"(ac), "r"(kA), "r"(kB), "n"(SM_CB - SM_CA), "n"(SM_C2 - SM_CA) : "memory");
            ac += 64; aoh += 32;
            ohnext = lds64(aoh);
            const uint32_t kA0 = prmt(kA, 0, 0x4140) * 0x3F80u, kA1 = prmt(kA, 0, 0x4342) * 0x3F80u;
            const uint32_t kB0 = prmt(kB, 0, 0x4140) * 0x3F80u, kB1 = prmt(kB, 0, 0x4342) * 0x3F80u;
            cp_async_wait<G_STAGES - 1>();
            __syncwarp();
            uint32_t a[4], b[4];
            ldsm_x4_trans(a, lsrc + ioff);
            ldsm_x4_trans(b, lsrc + ioff + 512);
            mma16816(D[0], a, mul_bf16x2(cA.x, kA0), mul_bf16x2(cA.y, kA1));
            mma16816(D[1], a, mul_bf16x2(cA.z, kA0), mul_bf16x2(cA.w, kA1));
            mma16816(D[2], a, mul_bf16x2(c2.x, kA0), mul_bf16x2(c2.y, kA1));
            mma16816(D[0], b, mul_bf16x2(cB.x, kB0), mul_bf16x2(cB.y, kB1));
            mma16816(D[1], b, mul_bf16x2(cB.z, kB0), mul_bf16x2(cB.w, kB1));
            mma16816(D[2], b, mul_bf16x2(c2.z, kB0), mul_bf16x2(c2.w, kB1));
        }
        uint32_t adown[4], aup[4], asbf[NL][2], arb[2];
        {
            const uint4* fr = reinterpret_cast<const uint4*>(g_frag) + lane;
            uint4 t0, t1, t2, t3;
            asm volatile("ld.global.nc.v4.u32 {%0,%1,%2,%3}, [%4];" : "=r"(t0.x), "=r"(t0.y), "=r"(t0.z), "=r"(t0.w) : "l"(fr));
            asm volatile("ld.global.nc.v4.u32 {%0,%1,%2,%3}, [%4];" : "=r"(t2.x), "=r"(t2.y), "=r"(t2.z), "=r"(t2.w) : "l"(fr + 64));
            asm volatile("ld.global.nc.v4.u32 {%0,%1,%2,%3}, [%4];" : "=r"(t3.x), "=r"(t3.y), "=r"(t3.z), "=r"(t3.w) : "l"(fr + 96));
            asm volatile("ld.global.nc.v4.u32 {%0,%1,%2,%3}, [%4];" : "=r"(t1.x), "=r"(t1.y), "=r"(t1.z), "=r"(t1.w) : "l"(fr + 32));
            adown[0] = t0.x; adown[1] = t0.y; adown[2] = t0.z; adown[3] = t0.w;
            aup[0] = t1.x; aup[1] = t1.y; aup[2] = t1.z; aup[3] = t1.w;
            asbf[0][0] = t2.x; asbf[0][1] = t2.y; asbf[1][0] = t2.z; asbf[1][1] = t2.w;
            asbf[2][0] = t3.x; asbf[2][1] = t3.y; arb[0] = t3.z; arb[1] = t3.w;
        }
        const uint32_t brbf = rbf_bf16x2(dg * 0x10001u, cen);
        float agg[4] = {0.f, 0.f, 0.f, 0.f};
#pragma unroll
        for (int l = 0; l < NL; l++) {
            const uint32_t h0 = movm(pack_bf16(D[l][0], D[l][1]));
            const uint32_t h1 = movm(pack_bf16(D[l][2], D[l][3]));
            float S[4] = {0.f, 0.f, 0.f, 0.f};
            float G[4] = {0.f, 0.f, 0.f, 0.f};
            mma16816(S, adown, h0, h1);
            mma1688(G, asbf[l], brbf);
#pragma unroll
            for (int c4 = 0; c4 < 4; c4++) agg[c4] = fmaf(S[c4], G[c4], agg[c4]);
        }
        if (ovf) {
            const int ea = ew + gi * 8 + 2 * q;
            if (va) {
                float* pa = g_ovf + (size_t)ea * DE + g;
                agg[0] += __ldcg(pa); agg[2] += __ldcg(pa + 8);
                pa[0] = 0.f; pa[8] = 0.f;
            }
            if (vb) {
                float* pb = g_ovf + (size_t)(ea + 1) * DE + g;
                agg[1] += __ldcg(pb); agg[3] += __ldcg(pb + 8);
                pb[0] = 0.f; pb[8] = 0.f;
            }
        }
        {
            const uint32_t h0 = movm(pack_bf16(agg[0], agg[1]));
            const uint32_t h1 = movm(pack_bf16(agg[2], agg[3]));
            float U[4] = {0.f, 0.f, 0.f, 0.f};
            float R[4] = {0.f, 0.f, 0.f, 0.f};
            mma16816(U, aup, h0, h1);
            mma1688(R, arb, brbf);
            uint32_t oa = pack_bf16(fmaf(U[0], R[0], bf16lo(ma)), fmaf(U[2], R[2], bf16hi(ma)));
            uint32_t ob = pack_bf16(fmaf(U[1], R[1], bf16lo(mbv)), fmaf(U[3], R[3], bf16hi(mbv)));
            unsigned char* ob8 = reinterpret_cast<unsigned char*>(p.out);
            if (va) *reinterpret_cast<uint32_t*>(ob8 + moff) = oa;
            if (vb) *reinterpret_cast<uint32_t*>(ob8 + moff + 32) = ob;
        }
    }
}

}

extern "C" void kernel_launch(void* const* d_in, const int* in_sizes, int n_in,
                              void* d_out, int out_size) {
    Params p;
    p.m = (const __nv_bfloat16*)d_in[0];
    p.idx_in = (const int*)d_in[1];
    p.idx_out = (const int*)d_in[2];
    p.dist = (const __nv_bfloat16*)d_in[3];
    p.angle = (const __nv_bfloat16*)d_in[4];
    p.centers = (const __nv_bfloat16*)d_in[5];
    p.ang_freq = (const __nv_bfloat16*)d_in[6];
    p.w_rbf = (const __nv_bfloat16*)d_in[7];
    p.w_sbf = (const __nv_bfloat16*)d_in[8];
    p.w_down = (const __nv_bfloat16*)d_in[9];
    p.w_up = (const __nv_bfloat16*)d_in[10];
    p.out = (__nv_bfloat16*)d_out;
    p.E = in_sizes[3];
    p.T = in_sizes[1];
    p.nbins = (p.E + NB - 1) / NB;

    const int smem1 = P_STAGE * 8 + (BINS_PAD + 4) * 4;
    const int smem2 = SM_TOTAL;
    static int nsm = 0;
    if (!nsm) {
        cudaFuncSetAttribute(k_partition, cudaFuncAttributeMaxDynamicSharedMemorySize, smem1);
        cudaFuncSetAttribute(k_gather, cudaFuncAttributeMaxDynamicSharedMemorySize, smem2);
        int dev = 0;
        cudaGetDevice(&dev);
        cudaDeviceGetAttribute(&nsm, cudaDevAttrMultiProcessorCount, dev);
    }
    p.nsm = nsm;
    long long per_sm = ((long long)p.T + nsm - 1) / nsm;
    int k = (int)((per_sm + P_TILE_MAX - 1) / P_TILE_MAX);
    if (k < 1) k = 1;
    long long tile = ((long long)p.T + (long long)k * nsm - 1) / ((long long)k * nsm);
    tile = (tile + 15) & ~15LL;
    if (tile > P_TILE_MAX) tile = P_TILE_MAX;
    if (tile < 16) tile = 16;
    p.tile = (int)tile;
    p.ntiles = (int)(((long long)p.T + tile - 1) / tile);
    int g1 = p.ntiles < nsm ? p.ntiles : nsm;
    if (g1 < 1) g1 = 1;
    k_partition<<<g1, P_NT, smem1>>>(p);
    k_gather<<<p.nbins, G_NT, smem2>>>(p);
}
```

```cpp
#include <cuda_runtime.h>
#include <cuda_bf16.h>
#include <stdint.h>

namespace {

constexpr int DE = 16;
constexpr int NR = 8;
constexpr int NL = 3;

constexpr int NB_LOG = 8;
constexpr int NB = 1 << NB_LOG;
constexpr int MAX_E = 400000;
constexpr int MAX_BINS = (MAX_E + NB - 1) / NB;
constexpr int BINS_PAD = 2048;
constexpr int CAPG = 5120;

constexpr int P_NT = 1024;
constexpr int P_PER = 16;
constexpr int P_TILE_MAX = P_NT * P_PER;
constexpr int P_STAGE = P_TILE_MAX + 3 * MAX_BINS + 16;

#define CFG_G_NT 256
#define CFG_G_BLOCKS 3
#define CFG_G_STAGES 2
#define CFG_P_PREFETCH 1
#define CFG_STAGGER_NS 0
#define CFG_PREFETCH 0
constexpr int G_NT = CFG_G_NT;
constexpr int G_BLOCKS = CFG_G_BLOCKS;
constexpr int G_PER = CAPG / G_NT;
constexpr int NGRP = NB / 8;
constexpr int CAPS = 5120;
constexpr int G_STAGES = CFG_G_STAGES;

__device__ uint2 g_records[(size_t)MAX_BINS * CAPG];
__device__ int g_cursor[BINS_PAD];
__device__ uint4 g_frag[4 * 32];
__device__ float g_ovf[(size_t)MAX_BINS * NB * DE];

__device__ __forceinline__ float bf16r(float x) { return __bfloat162float(__float2bfloat16_rn(x)); }
__device__ __forceinline__ float bf16lo(uint32_t v) { return __uint_as_float(v << 16); }
__device__ __forceinline__ float bf16hi(uint32_t v) { return __uint_as_float(v & 0xffff0000u); }
__device__ __forceinline__ float ldbf(const __nv_bfloat16* p) { return __bfloat162float(*p); }
__device__ __forceinline__ uint32_t smem_u32(const void* p) { return (uint32_t)__cvta_generic_to_shared(p); }

__device__ __forceinline__ uint32_t pack_bf16(float lo, float hi) {
    __nv_bfloat162 v = __floats2bfloat162_rn(lo, hi);
    return *reinterpret_cast<uint32_t*>(&v);
}
__device__ __forceinline__ uint32_t mul_bf16x2(uint32_t a, uint32_t b) {
    __nv_bfloat162 r = __hmul2(*reinterpret_cast<__nv_bfloat162*>(&a), *reinterpret_cast<__nv_bfloat162*>(&b));
    return *reinterpret_cast<uint32_t*>(&r);
}
__device__ __forceinline__ uint32_t sub_bf16x2(uint32_t a, uint32_t b) {
    __nv_bfloat162 r = __hsub2(*reinterpret_cast<__nv_bfloat162*>(&a), *reinterpret_cast<__nv_bfloat162*>(&b));
    return *reinterpret_cast<uint32_t*>(&r);
}
__device__ __forceinline__ uint32_t cos_fast_bf16x2(uint32_t x) {
    return pack_bf16(__cosf(bf16lo(x)), __cosf(bf16hi(x)));
}
__device__ __noinline__ uint32_t cos_slow_bf16x2(uint32_t x) {
    return pack_bf16(cosf(bf16lo(x)), cosf(bf16hi(x)));
}
__device__ __forceinline__ uint32_t rbf_bf16x2(uint32_t dd, uint32_t cc) {
    uint32_t t = sub_bf16x2(dd, cc);
    t = mul_bf16x2(t, t);
    t = mul_bf16x2(t, 0xC120C120u);
    return pack_bf16(__expf(bf16lo(t)), __expf(bf16hi(t)));
}

__device__ __forceinline__ void mma16816(float* d, const uint32_t* a, uint32_t b0, uint32_t b1) {
    asm volatile("mma.sync.aligned.m16n8k16.row.col.f32.bf16.bf16.f32 {%0,%1,%2,%3}, {%4,%5,%6,%7}, {%8,%9}, {%0,%1,%2,%3};"
                 : "+f"(d[0]), "+f"(d[1]), "+f"(d[2]), "+f"(d[3])
                 : "r"(a[0]), "r"(a[1]), "r"(a[2]), "r"(a[3]), "r"(b0), "r"(b1));
}
__device__ __forceinline__ void mma1688(float* d, const uint32_t* a, uint32_t b) {
    asm volatile("mma.sync.aligned.m16n8k8.row.col.f32.bf16.bf16.f32 {%0,%1,%2,%3}, {%4,%5}, {%6}, {%0,%1,%2,%3};"
                 : "+f"(d[0]), "+f"(d[1]), "+f"(d[2]), "+f"(d[3])
                 : "r"(a[0]), "r"(a[1]), "r"(b));
}
__device__ __forceinline__ uint32_t movm(uint32_t a) {
    uint32_t d;
    asm volatile("movmatrix.sync.aligned.m8n8.trans.b16 %0, %1;" : "=r"(d) : "r"(a));
    return d;
}
__device__ __forceinline__ uint32_t prmt(uint32_t a, uint32_t b, uint32_t sel) {
    uint32_t d;
    asm("prmt.b32 %0, %1, %2, %3;" : "=r"(d) : "r"(a), "r"(b), "r"(sel));
    return d;
}
__device__ __forceinline__ void ldsm_x4_trans(uint32_t* r, uint32_t addr) {
    asm volatile("ldmatrix.sync.aligned.m8n8.x4.trans.shared.b16 {%0,%1,%2,%3}, [%4];"
                 : "=r"(r[0]), "=r"(r[1]), "=r"(r[2]), "=r"(r[3]) : "r"(addr) : "memory");
}
__device__ __forceinline__ void cp_async_row(uint32_t dst, const unsigned char* base, uint32_t w) {
    uint64_t addr;
    asm("mad.wide.u32 %0, %1, 1, %2;" : "=l"(addr) : "r"(w & 0xffffffu), "l"(base));
    asm volatile("{ .reg .pred p; setp.gt.u32 p, %2, 0xffffff; @p cp.async.cg.shared.global [%0], [%1], 16; }" :: "r"(dst), "l"(addr), "r"(w) : "memory");
}
__device__ __forceinline__ void cp_async_commit() { asm volatile("cp.async.commit_group;" ::: "memory"); }
template <int N> __device__ __forceinline__ void cp_async_wait() { asm volatile("cp.async.wait_group %0;" :: "n"(N) : "memory"); }

struct Params {
    const __nv_bfloat16* m;
    const int* idx_in;
    const int* idx_out;
    const __nv_bfloat16* dist;
    const __nv_bfloat16* angle;
    const __nv_bfloat16* centers;
    const __nv_bfloat16* ang_freq;
    const __nv_bfloat16* w_rbf;
    const __nv_bfloat16* w_sbf;
    const __nv_bfloat16* w_down;
    const __nv_bfloat16* w_up;
    __nv_bfloat16* out;
    int E, T, nbins, ntiles, tile, nsm;
};

__device__ __noinline__ void slow_bin(const Params* pp, int bin) {
    const Params& p = *pp;
    for (int t = threadIdx.x; t < p.T; t += blockDim.x) {
        const int out = p.idx_out[t];
        if ((out >> NB_LOG) != bin) continue;
        const int in = p.idx_in[t];
        const float ang = ldbf(p.angle + t);
        float mrow[DE], rb[NR], cb[NL];
        for (int k = 0; k < DE; k++) mrow[k] = ldbf(p.m + (size_t)in * DE + k);
        float d = ldbf(p.dist + out);
        for (int r = 0; r < NR; r++) {
            float u = bf16r(d - ldbf(p.centers + r));
            u = bf16r(u * u);
            u = bf16r(-10.0f * u);
            rb[r] = bf16r(__expf(u));
        }
        for (int l = 0; l < NL; l++) cb[l] = bf16r(cosf(bf16r(ldbf(p.ang_freq + l) * ang)));
        for (int c = 0; c < DE; c++) {
            float md = 0.f, s = 0.f;
            for (int k = 0; k < DE; k++) md = fmaf(mrow[k], ldbf(p.w_down + k * DE + c), md);
            for (int r = 0; r < NR; r++)
                for (int l = 0; l < NL; l++) s = fmaf(rb[r] * cb[l], ldbf(p.w_sbf + (r * NL + l) * DE + c), s);
            atomicAdd(&g_ovf[(size_t)out * DE + c], md * s);
        }
    }
    __threadfence();
}

__device__ __forceinline__ int4 ld4_guard(const int* p, int i, int n, int fill) {
    if (i + 3 < n) return __ldcs(reinterpret_cast<const int4*>(p + i));
    int4 r;
    r.x = (i + 0 < n) ? p[i + 0] : fill;
    r.y = (i + 1 < n) ? p[i + 1] : fill;
    r.z = (i + 2 < n) ? p[i + 2] : fill;
    r.w = fill;
    return r;
}
__device__ __forceinline__ uint2 ld4h_guard(const unsigned short* p, int i, int n) {
    if (i + 3 < n) return __ldcs(reinterpret_cast<const uint2*>(p + i));
    uint32_t a = (i + 0 < n) ? p[i + 0] : 0u, b = (i + 1 < n) ? p[i + 1] : 0u, c = (i + 2 < n) ? p[i + 2] : 0u;
    return make_uint2(a | (b << 16), c);
}

__device__ __forceinline__ void prefetch_tile(const Params& p, int tile, int which) {
    const int base = tile * p.tile;
    const int n = min(p.tile, p.T - base) & ~7;
    if (n <= 0) return;
    if (which == 0) asm volatile("cp.async.bulk.prefetch.L2.global [%0], %1;" :: "l"(p.idx_out + base), "r"(n * 4) : "memory");
    if (which == 1) asm volatile("cp.async.bulk.prefetch.L2.global [%0], %1;" :: "l"(p.idx_in + base), "r"(n * 4) : "memory");
    if (which == 2) asm volatile("cp.async.bulk.prefetch.L2.global [%0], %1;" :: "l"(p.angle + base), "r"(n * 2) : "memory");
}

__global__ void __launch_bounds__(P_NT, 1) k_partition(const __grid_constant__ Params p) {
    extern __shared__ __align__(16) unsigned char smem_raw[];
    uint2* stage = reinterpret_cast<uint2*>(smem_raw);
    int* hist = reinterpret_cast<int*>(smem_raw + (size_t)P_STAGE * 8);
    __shared__ int warp_sums[P_NT / 32];
    static_assert(BINS_PAD == 2 * P_NT, "two bins per thread in the scan");

    const int tid = threadIdx.x;
    const int lane = tid & 31, wid = tid >> 5;
    const unsigned short* ang16 = reinterpret_cast<const unsigned short*>(p.angle);

    if (blockIdx.x == 0 && wid == P_NT / 32 - 1) {
        const int g = lane >> 2, q = lane & 3;
        const unsigned short* wd = reinterpret_cast<const unsigned short*>(p.w_down);
        const unsigned short* wu = reinterpret_cast<const unsigned short*>(p.w_up);
        const unsigned short* ws = reinterpret_cast<const unsigned short*>(p.w_sbf);
        const unsigned short* wr = reinterpret_cast<const unsigned short*>(p.w_rbf);
        uint4 t;
        t.x = (uint32_t)wd[(2 * q) * DE + g] | ((uint32_t)wd[(2 * q + 1) * DE + g] << 16);
        t.y = (uint32_t)wd[(2 * q) * DE + g + 8] | ((uint32_t)wd[(2 * q + 1) * DE + g + 8] << 16);
        t.z = (uint32_t)wd[(2 * q + 8) * DE + g] | ((uint32_t)wd[(2 * q + 9) * DE + g] << 16);
        t.w = (uint32_t)wd[(2 * q + 8) * DE + g + 8] | ((uint32_t)wd[(2 * q + 9) * DE + g + 8] << 16);
        g_frag[lane] = t;
        const int cA = 2 * g, cB = 2 * g + 1;
        t.x = (uint32_t)wu[(2 * q) * DE + cA] | ((uint32_t)wu[(2 * q + 1) * DE + cA] << 16);
        t.y = (uint32_t)wu[(2 * q) * DE + cB] | ((uint32_t)wu[(2 * q + 1) * DE + cB] << 16);
        t.z = (uint32_t)wu[(2 * q + 8) * DE + cA] | ((uint32_t)wu[(2 * q + 9) * DE + cA] << 16);
        t.w = (uint32_t)wu[(2 * q + 8) * DE + cB] | ((uint32_t)wu[(2 * q + 9) * DE + cB] << 16);
        g_frag[32 + lane] = t;
        uint32_t sb[NL][2];
#pragma unroll
        for (int l = 0; l < NL; l++) {
            sb[l][0] = (uint32_t)ws[((2 * q) * NL + l) * DE + g] | ((uint32_t)ws[((2 * q + 1) * NL + l) * DE + g] << 16);
            sb[l][1] = (uint32_t)ws[((2 * q) * NL + l) * DE + g + 8] | ((uint32_t)ws[((2 * q + 1) * NL + l) * DE + g + 8] << 16);
        }
        g_frag[64 + lane] = make_uint4(sb[0][0], sb[0][1], sb[1][0], sb[1][1]);
        t.x = sb[2][0]; t.y = sb[2][1];
        t.z = (uint32_t)wr[(2 * q) * DE + cA] | ((uint32_t)wr[(2 * q + 1) * DE + cA] << 16);
        t.w = (uint32_t)wr[(2 * q) * DE + cB] | ((uint32_t)wr[(2 * q + 1) * DE + cB] << 16);
        g_frag[96 + lane] = t;
    }

    int4 O[P_PER / 4];
    int tile = blockIdx.x;
    if (tile < p.ntiles && (tid == 32 || tid == 64)) prefetch_tile(p, tile, tid >> 5);
    if (tile < p.ntiles) {
        const int base = tile * p.tile, n = min(p.tile, p.T - base);
#pragma unroll
        for (int v = 0; v < P_PER / 4; v++) O[v] = ld4_guard(p.idx_out + base, (v * P_NT + tid) * 4, n, -1);
    }
    reinterpret_cast<int2*>(hist)[tid] = make_int2(0, 0);
    if (tid == 0) hist[BINS_PAD] = 0;
    for (; tile < p.ntiles; tile += gridDim.x) {
        const int base = tile * p.tile, n = min(p.tile, p.T - base);
        if (tile + (int)gridDim.x < p.ntiles && (tid & 31) == 0 && wid < 3) prefetch_tile(p, tile + gridDim.x, wid);
        __syncthreads();
#pragma unroll
        for (int v = 0; v < P_PER / 4; v++) {
            atomicAdd(&hist[min((uint32_t)O[v].x >> NB_LOG, (uint32_t)BINS_PAD)], 1);
            atomicAdd(&hist[min((uint32_t)O[v].y >> NB_LOG, (uint32_t)BINS_PAD)], 1);
            atomicAdd(&hist[min((uint32_t)O[v].z >> NB_LOG, (uint32_t)BINS_PAD)], 1);
            atomicAdd(&hist[min((uint32_t)O[v].w >> NB_LOG, (uint32_t)BINS_PAD)], 1);
        }
        int4 I[P_PER / 4];
        uint2 A[P_PER / 4];
#pragma unroll
        for (int v = 0; v < P_PER / 4; v++) {
            I[v] = ld4_guard(p.idx_in + base, (v * P_NT + tid) * 4, n, 0);
            A[v] = ld4h_guard(ang16 + base, (v * P_NT + tid) * 4, n);
        }
        __syncthreads();
        const int2 c2 = reinterpret_cast<int2*>(hist)[tid];
        const int pc0 = (c2.x + 3) & ~3, pc1 = (c2.y + 3) & ~3;
        int g0 = 0, g1 = 0;
        if (pc0) g0 = atomicAdd(&g_cursor[2 * tid], pc0);
        if (pc1) g1 = atomicAdd(&g_cursor[2 * tid + 1], pc1);
        const int s = pc0 + pc1;
        int inc = s;
#pragma unroll
        for (int o = 1; o < 32; o <<= 1) {
            int t = __shfl_up_sync(0xffffffffu, inc, o);
            if (lane >= o) inc += t;
        }
        if (lane == 31) warp_sums[wid] = inc;
        asm volatile("cp.async.bulk.wait_group.read 0;" ::: "memory");
        __syncthreads();
        int woff;
        {
            int ws = warp_sums[lane];
            int winc = ws;
#pragma unroll
            for (int o = 1; o < 32; o <<= 1) {
                int t = __shfl_up_sync(0xffffffffu, winc, o);
                if (lane >= o) winc += t;
            }
            woff = __shfl_sync(0xffffffffu, winc - ws, wid);
        }
        const int e0 = woff + inc - s, e1 = e0 + pc0;
        reinterpret_cast<int2*>(hist)[tid] = make_int2(e0, e1);
        if (tid == 0) hist[BINS_PAD] = P_STAGE;
        for (int k = c2.x; k < pc0; k++) stage[e0 + k] = make_uint2(0u, 0xffffffffu);
        for (int k = c2.y; k < pc1; k++) stage[e1 + k] = make_uint2(0u, 0xffffffffu);
        __syncthreads();
#pragma unroll
        for (int v = 0; v < P_PER / 4; v++) {
            const uint32_t o[4] = {(uint32_t)O[v].x, (uint32_t)O[v].y, (uint32_t)O[v].z, (uint32_t)O[v].w};
            const uint32_t in[4] = {(uint32_t)I[v].x, (uint32_t)I[v].y, (uint32_t)I[v].z, (uint32_t)I[v].w};
            const uint32_t an[4] = {A[v].x & 0xffffu, A[v].x >> 16, A[v].y & 0xffffu, A[v].y >> 16};
#pragma unroll
            for (int u = 0; u < 4; u++) {
                int pos = atomicAdd(&hist[min(o[u] >> NB_LOG, (uint32_t)BINS_PAD)], 1);
                stage[min(pos, P_STAGE - 1)] = make_uint2((in[u] << 5) | (0x1000000u << (o[u] & 7)), an[u] | ((o[u] & 255u) << 16));
            }
        }
        {
            const int nt = tile + gridDim.x;
            if (nt < p.ntiles) {
                const int nbase = nt * p.tile, nn = min(p.tile, p.T - nbase);
#pragma unroll
                for (int v = 0; v < P_PER / 4; v++) O[v] = ld4_guard(p.idx_out + nbase, (v * P_NT + tid) * 4, nn, -1);
            }
        }
        asm volatile("fence.proxy.async.shared::cta;" ::: "memory");
        __syncthreads();
        if (pc0 && g0 + pc0 <= CAPG)
            asm volatile("cp.async.bulk.global.shared::cta.bulk_group [%0], [%1], %2;"
                         :: "l"(g_records + (size_t)(2 * tid) * CAPG + g0), "r"(smem_u32(stage + e0)), "r"(pc0 * 8) : "memory");
        if (pc1 && g1 + pc1 <= CAPG)
            asm volatile("cp.async.bulk.global.shared::cta.bulk_group [%0], [%1], %2;"
                         :: "l"(g_records + (size_t)(2 * tid + 1) * CAPG + g1), "r"(smem_u32(stage + e1)), "r"(pc1 * 8) : "memory");
        asm volatile("cp.async.bulk.commit_group;" ::: "memory");
        reinterpret_cast<int2*>(hist)[tid] = make_int2(0, 0);
        if (tid == 0) hist[BINS_PAD] = 0;
    }
    asm volatile("cp.async.bulk.wait_group 0;" ::: "memory");
}

constexpr int NOCT = CAPS / 8;
constexpr int SM_IDX = 0;
constexpr int SM_CA = SM_IDX + (CAPS + 32) * 4;
constexpr int SM_CB = SM_CA + NOCT * 16;
constexpr int SM_C2 = SM_CB + NOCT * 16;
constexpr int SM_OH = SM_C2 + (NOCT + 4) * 16;
constexpr int SM_RING = SM_OH + (NOCT + 8) * 8;
constexpr int SM_TOTAL = SM_RING + (G_NT / 32) * G_STAGES * 1024;

__device__ __forceinline__ uint2 lds64(uint32_t a) { uint2 v; asm volatile("ld.shared.v2.u32 {%0,%1}, [%2];" : "=r"(v.x), "=r"(v.y) : "r"(a) : "memory"); return v; }

__global__ void __launch_bounds__(G_NT, G_BLOCKS) k_gather(const __grid_constant__ Params p) {
    extern __shared__ __align__(128) unsigned char smem_raw[];
    uint32_t* sidx = reinterpret_cast<uint32_t*>(smem_raw + SM_IDX);
    uint4* scA = reinterpret_cast<uint4*>(smem_raw + SM_CA);
    uint4* scB = reinterpret_cast<uint4*>(smem_raw + SM_CB);
    unsigned short* sang = reinterpret_cast<unsigned short*>(smem_raw + SM_C2);
    uint2* soh = reinterpret_cast<uint2*>(smem_raw + SM_OH);
    __shared__ int cnts[NB + 32];
    __shared__ int gstart[NGRP + 1];
    __shared__ int warp_sums[NB / 32];

    const int tid = threadIdx.x;
    const int lane = tid & 31, wid = tid >> 5;
    const int bin = blockIdx.x;
    const int total = g_cursor[bin];
    bool ovf = total > CAPG;
    const int n = ovf ? 0 : total;

    const uint4* rec = reinterpret_cast<const uint4*>(g_records + (size_t)bin * CAPG) + tid;
    uint4 r[G_PER / 2];
#pragma unroll
    for (int j = 0; j < G_PER / 2; j++) {
        r[j] = make_uint4(0u, 0xffffffffu, 0u, 0xffffffffu);
        if ((j * G_NT + tid) * 2 < n) r[j] = __ldcs(rec + j * G_NT);
    }
    if (tid < NB) cnts[tid] = 0;
    for (int i = tid; i < (G_NT / 32) * G_STAGES * 64; i += G_NT)
        reinterpret_cast<uint4*>(smem_raw + SM_RING)[i] = make_uint4(0u, 0u, 0u, 0u);
    const unsigned short* fq = reinterpret_cast<const unsigned short*>(p.ang_freq);
    const uint32_t f0 = (uint32_t)fq[0] * 0x10001u, f1 = (uint32_t)fq[1] * 0x10001u, f2 = (uint32_t)fq[2] * 0x10001u;
    const uint32_t fmaxp = max(max(f0 & 0x7fff7fffu, f1 & 0x7fff7fffu), f2 & 0x7fff7fffu);
    const uint32_t dkey = NB + lane;
    __syncthreads();
    if (tid == 0) g_cursor[bin] = 0;
#pragma unroll
    for (int j = 0; j < G_PER / 2; j++) {
        atomicAdd(&cnts[min(r[j].y >> 16, dkey)], 1);
        atomicAdd(&cnts[min(r[j].w >> 16, dkey)], 1);
    }
    __syncthreads();
    int c = 0, inc = 0, cp = 0, npad = 0;
    if (tid < NB) {
        c = cnts[tid];
        int gt = c;
        gt += __shfl_xor_sync(0xffffffffu, gt, 1);
        gt += __shfl_xor_sync(0xffffffffu, gt, 2);
        gt += __shfl_xor_sync(0xffffffffu, gt, 4);
        npad = ((gt + 31) & ~31) - gt;
        cp = c + (((lane & 7) == 7) ? npad : 0);
        inc = cp;
#pragma unroll
        for (int o = 1; o < 32; o <<= 1) {
            int t = __shfl_up_sync(0xffffffffu, inc, o);
            if (lane >= o) inc += t;
        }
        if (lane == 31) warp_sums[wid] = inc;
    }
    __syncthreads();
    {
        int woff = 0, tot = 0;
#pragma unroll
        for (int w = 0; w < NB / 32; w++) { woff += (w < wid) ? warp_sums[w] : 0; tot += warp_sums[w]; }
        ovf = ovf || (tot > CAPS);
        if (tid < NB) {
            const int st = ovf ? 0 : woff + inc - cp;
            cnts[tid] = ovf ? CAPS : st;
            if ((lane & 7) == 0) gstart[tid >> 3] = st;
            if (tid == NB - 1) gstart[NGRP] = ovf ? 0 : tot;
            if (tid < 32) cnts[NB + tid] = CAPS;
            const int gend = __shfl_sync(0xffffffffu, woff + inc, lane | 7);
            if (!ovf) {
#pragma unroll
                for (int k = 0; k < 4; k++) {
                    const int kk = (lane & 7) + 8 * k;
                    if (kk < npad) { sidx[gend - 1 - kk] = 0u; sang[gend - 1 - kk] = 0; }
                }
            }
        }
    }
    __syncthreads();
#pragma unroll
    for (int j = 0; j < G_PER / 2; j++) {
        {
            const int pos = min(atomicAdd(&cnts[min(r[j].y >> 16, dkey)], 1), CAPS);
            sidx[pos] = r[j].x;
            sang[pos] = (unsigned short)r[j].y;
        }
        {
            const int pos = min(atomicAdd(&cnts[min(r[j].w >> 16, dkey)], 1), CAPS);
            sidx[pos] = r[j].z;
            sang[pos] = (unsigned short)r[j].w;
        }
    }
    if (ovf) slow_bin(&p, bin);
    __syncthreads();

    const int g = lane >> 2, q = lane & 3;
    constexpr int GPW = NGRP / (G_NT / 32);
    const int grp0 = wid * GPW;
    const int wbeg = gstart[grp0], wend = gstart[grp0 + GPW];
    const unsigned char* mb = reinterpret_cast<const unsigned char*>(p.m);
    const uint32_t sbase = smem_u32(smem_raw);

    const uint32_t ring = sbase + SM_RING + wid * (G_STAGES * 1024);
    const int cj = lane >> 1;
    const int crow = (cj >> 2) * 2 + (cj & 1) + ((cj >> 1) & 1) * 8;
    const uint32_t cdst = ring + (uint32_t)(crow * 32 + (((lane ^ (crow >> 2)) & 1) * 16));
    const unsigned char* msrc = mb + (lane & 1) * 16;
    const int lrow = (lane >> 4) * 8 + (lane & 7);
    const uint32_t lsrc = ring + (uint32_t)(lrow * 32 + ((((lane >> 3) ^ (lrow >> 2)) & 1) * 16));

    uint32_t iaddr = sbase + SM_IDX + (wbeg + 2 * cj) * 4;
    const uint32_t iend = sbase + SM_IDX + wend * 4;
    uint32_t ioff = 0;
#pragma unroll
    for (int k = 0; k < G_STAGES - 1; k++) {
        if (iaddr < iend) {
            const uint2 w = lds64(iaddr);
            cp_async_row(cdst + ioff, msrc, w.x);
            cp_async_row(cdst + ioff + 512, msrc, w.y);
        }
        cp_async_commit();
        iaddr += 128; ioff += 1024;
    }

    {
        const int noct = gstart[NGRP] >> 3;
        for (int i = tid; i < noct; i += G_NT) {
            const uint4 an = reinterpret_cast<const uint4*>(sang)[i];
            const uint4 w0 = reinterpret_cast<const uint4*>(sidx)[2 * i];
            const uint4 w1 = reinterpret_cast<const uint4*>(sidx)[2 * i + 1];
            soh[i] = make_uint2(prmt(prmt(w0.x, w0.z, 0x0073), prmt(w1.x, w1.z, 0x0073), 0x5410),
                                prmt(prmt(w0.y, w0.w, 0x0073), prmt(w1.y, w1.w, 0x0073), 0x5410));
            const uint32_t aA0 = prmt(an.x, an.y, 0x5410), aA1 = prmt(an.z, an.w, 0x5410);
            const uint32_t aB0 = prmt(an.x, an.y, 0x7632), aB1 = prmt(an.z, an.w, 0x7632);
            const uint32_t amax = __vmaxu2(__vmaxu2(an.x & 0x7fff7fffu, an.y & 0x7fff7fffu), __vmaxu2(an.z & 0x7fff7fffu, an.w & 0x7fff7fffu));
            const uint32_t t = mul_bf16x2(amax, fmaxp);
            uint4 oA, oB, o2;
            if ((t >> 16) < 0x4300u && (t & 0xffffu) < 0x4300u) {
                oA.x = cos_fast_bf16x2(mul_bf16x2(aA0, f0)); oA.y = cos_fast_bf16x2(mul_bf16x2(aA1, f0));
                oA.z = cos_fast_bf16x2(mul_bf16x2(aA0, f1)); oA.w = cos_fast_bf16x2(mul_bf16x2(aA1, f1));
                oB.x = cos_fast_bf16x2(mul_bf16x2(aB0, f0)); oB.y = cos_fast_bf16x2(mul_bf16x2(aB1, f0));
                oB.z = cos_fast_bf16x2(mul_bf16x2(aB0, f1)); oB.w = cos_fast_bf16x2(mul_bf16x2(aB1, f1));
                o2.x = cos_fast_bf16x2(mul_bf16x2(aA0, f2)); o2.y = cos_fast_bf16x2(mul_bf16x2(aA1, f2));
                o2.z = cos_fast_bf16x2(mul_bf16x2(aB0, f2)); o2.w = cos_fast_bf16x2(mul_bf16x2(aB1, f2));
            } else {
                oA.x = cos_slow_bf16x2(mul_bf16x2(aA0, f0)); oA.y = cos_slow_bf16x2(mul_bf16x2(aA1, f0));
                oA.z = cos_slow_bf16x2(mul_bf16x2(aA0, f1)); oA.w = cos_slow_bf16x2(mul_bf16x2(aA1, f1));
                oB.x = cos_slow_bf16x2(mul_bf16x2(aB0, f0)); oB.y = cos_slow_bf16x2(mul_bf16x2(aB1, f0));
                oB.z = cos_slow_bf16x2(mul_bf16x2(aB0, f1)); oB.w = cos_slow_bf16x2(mul_bf16x2(aB1, f1));
                o2.x = cos_slow_bf16x2(mul_bf16x2(aA0, f2)); o2.y = cos_slow_bf16x2(mul_bf16x2(aA1, f2));
                o2.z = cos_slow_bf16x2(mul_bf16x2(aB0, f2)); o2.w = cos_slow_bf16x2(mul_bf16x2(aB1, f2));
            }
            scA[i] = oA;
            scB[i] = oB;
            reinterpret_cast<uint4*>(sang)[i] = o2;
        }
    }

    const uint32_t cen = reinterpret_cast<const uint32_t*>(p.centers)[q];

    const int ew = bin * NB + grp0 * 8;
    const unsigned short* pdist = reinterpret_cast<const unsigned short*>(p.dist) + ew + g;
    const uint32_t moff0 = (uint32_t)(ew + 2 * q) * 32u + 4u * g;
    const int nleft = p.E - ew;
    uint32_t dgn = (g < nleft) ? (uint32_t)pdist[0] : 0u;
    uint32_t man = (2 * q < nleft) ? __ldg(reinterpret_cast<const uint32_t*>(mb + moff0)) : 0u;
    uint32_t mbn = (2 * q + 1 < nleft) ? __ldg(reinterpret_cast<const uint32_t*>(mb + moff0 + 32)) : 0u;
    __syncthreads();

    uint2 wnext = make_uint2(0u, 0u);
    if (iaddr < iend) wnext = lds64(iaddr);
    uint32_t ac = sbase + SM_CA + ((wbeg >> 3) + q) * 16;
    uint32_t aoh = sbase + SM_OH + ((wbeg >> 3) + q) * 8;
    uint2 ohnext = lds64(aoh);
    uint4 cA = make_uint4(0u, 0u, 0u, 0u), cB = cA, c2 = cA;
#pragma unroll 1
    for (int gi = 0; gi < GPW; gi++) {
        const uint32_t aend = sbase + SM_OH + (uint32_t)gstart[grp0 + gi + 1];
        const uint32_t moff = moff0 + gi * 256;
        const bool va = gi * 8 + 2 * q < nleft, vb = gi * 8 + 2 * q + 1 < nleft;
        const uint32_t dg = dgn, ma = man, mbv = mbn;
        if (gi + 1 < GPW) {
            dgn = (gi * 8 + 8 + g < nleft) ? (uint32_t)pdist[gi * 8 + 8] : 0u;
            man = (gi * 8 + 8 + 2 * q < nleft) ? __ldg(reinterpret_cast<const uint32_t*>(mb + moff + 256)) : 0u;
            mbn = (gi * 8 + 9 + 2 * q < nleft) ? __ldg(reinterpret_cast<const uint32_t*>(mb + moff + 288)) : 0u;
        }

        float D[NL][4];
#pragma unroll
        for (int l = 0; l < NL; l++)
#pragma unroll
            for (int c4 = 0; c4 < 4; c4++) D[l][c4] = 0.f;
#pragma unroll 1
        while (aoh < aend) {
            cp_async_row(cdst + ioff, msrc, wnext.x);
            cp_async_row(cdst + ioff + 512, msrc, wnext.y);
            cp_async_commit();
            iaddr += 128; ioff = (ioff == (G_STAGES - 1) * 1024) ? 0 : ioff + 1024;
            wnext = make_uint2(0u, 0u);
            if (iaddr < iend) wnext = lds64(iaddr);
            const uint32_t kA = (ohnext.x >> g) & 0x01010101u, kB = (ohnext.y >> g) & 0x01010101u;
            asm volatile("{ .reg .pred pa, pb, pc; setp.ne.u32 pa, %13, 0; setp.ne.u32 pb, %14, 0; or.pred pc, pa, pb;\n\t"
                         "@pa ld.shared.v4.u32 {%0,%1,%2,%3}, [%12];\n\t"
                         "@pb ld.shared.v4.u32 {%4,%5,%6,%7}, [%12+%15];\n\t"
                         "@pc ld.shared.v4.u32 {%8,%9,%10,%11}, [%12+%16]; }"
                         : "+r"(cA.x), "+r"(cA.y), "+r"(cA.z), "+r"(cA.w), "+r"(cB.x), "+r"(cB.y), "+r"(cB.z), "+r"(cB.w),
                           "+r"(c2.x), "+r"(c2.y), "+r"(c2.z), "+r"(c2.w)
                         : "r"(ac), "r"(kA), "r"(kB), "n"(SM_CB - SM_CA), "n"(SM_C2 - SM_CA) : "memory");
            ac += 64; aoh += 32;
            ohnext = lds64(aoh);
            const uint32_t kA0 = prmt(kA, 0, 0x4140) * 0x3F80u, kA1 = prmt(kA, 0, 0x4342) * 0x3F80u;
            const uint32_t kB0 = prmt(kB, 0, 0x4140) * 0x3F80u, kB1 = prmt(kB, 0, 0x4342) * 0x3F80u;
            cp_async_wait<G_STAGES - 1>();
            __syncwarp();
            uint32_t a[4], b[4];
            ldsm_x4_trans(a, lsrc + ioff);
            ldsm_x4_trans(b, lsrc + ioff + 512);
            mma16816(D[0], a, mul_bf16x2(cA.x, kA0), mul_bf16x2(cA.y, kA1));
            mma16816(D[1], a, mul_bf16x2(cA.z, kA0), mul_bf16x2(cA.w, kA1));
            mma16816(D[2], a, mul_bf16x2(c2.x, kA0), mul_bf16x2(c2.y, kA1));
            mma16816(D[0], b, mul_bf16x2(cB.x, kB0), mul_bf16x2(cB.y, kB1));
            mma16816(D[1], b, mul_bf16x2(cB.z, kB0), mul_bf16x2(cB.w, kB1));
            mma16816(D[2], b, mul_bf16x2(c2.z, kB0), mul_bf16x2(c2.w, kB1));
        }
        uint32_t adown[4], aup[4], asbf[NL][2], arb[2];
        {
            const uint4* fr = reinterpret_cast<const uint4*>(g_frag) + lane;
            uint4 t0, t1, t2, t3;
            asm volatile("ld.global.nc.v4.u32 {%0,%1,%2,%3}, [%4];" : "=r"(t0.x), "=r"(t0.y), "=r"(t0.z), "=r"(t0.w) : "l"(fr));
            asm volatile("ld.global.nc.v4.u32 {%0,%1,%2,%3}, [%4];" : "=r"(t2.x), "=r"(t2.y), "=r"(t2.z), "=r"(t2.w) : "l"(fr + 64));
            asm volatile("ld.global.nc.v4.u32 {%0,%1,%2,%3}, [%4];" : "=r"(t3.x), "=r"(t3.y), "=r"(t3.z), "=r"(t3.w) : "l"(fr + 96));
            asm volatile("ld.global.nc.v4.u32 {%0,%1,%2,%3}, [%4];" : "=r"(t1.x), "=r"(t1.y), "=r"(t1.z), "=r"(t1.w) : "l"(fr + 32));
            adown[0] = t0.x; adown[1] = t0.y; adown[2] = t0.z; adown[3] = t0.w;
            aup[0] = t1.x; aup[1] = t1.y; aup[2] = t1.z; aup[3] = t1.w;
            asbf[0][0] = t2.x; asbf[0][1] = t2.y; asbf[1][0] = t2.z; asbf[1][1] = t2.w;
            asbf[2][0] = t3.x; asbf[2][1] = t3.y; arb[0] = t3.z; arb[1] = t3.w;
        }
        const uint32_t brbf = rbf_bf16x2(dg * 0x10001u, cen);
        float agg[4] = {0.f, 0.f, 0.f, 0.f};
#pragma unroll
        for (int l = 0; l < NL; l++) {
            const uint32_t h0 = movm(pack_bf16(D[l][0], D[l][1]));
            const uint32_t h1 = movm(pack_bf16(D[l][2], D[l][3]));
            float S[4] = {0.f, 0.f, 0.f, 0.f};
            float G[4] = {0.f, 0.f, 0.f, 0.f};
            mma16816(S, adown, h0, h1);
            mma1688(G, asbf[l], brbf);
#pragma unroll
            for (int c4 = 0; c4 < 4; c4++) agg[c4] = fmaf(S[c4], G[c4], agg[c4]);
        }
        if (ovf) {
            const int ea = ew + gi * 8 + 2 * q;
            if (va) {
                float* pa = g_ovf + (size_t)ea * DE + g;
                agg[0] += __ldcg(pa); agg[2] += __ldcg(pa + 8);
                pa[0] = 0.f; pa[8] = 0.f;
            }
            if (vb) {
                float* pb = g_ovf + (size_t)(ea + 1) * DE + g;
                agg[1] += __ldcg(pb); agg[3] += __ldcg(pb + 8);
                pb[0] = 0.f; pb[8] = 0.f;
            }
        }
        {
            const uint32_t h0 = movm(pack_bf16(agg[0], agg[1]));
            const uint32_t h1 = movm(pack_bf16(agg[2], agg[3]));
            float U[4] = {0.f, 0.f, 0.f, 0.f};
            float R[4] = {0.f, 0.f, 0.f, 0.f};
            mma16816(U, aup, h0, h1);
            mma1688(R, arb, brbf);
            uint32_t oa = pack_bf16(fmaf(U[0], R[0], bf16lo(ma)), fmaf(U[2], R[2], bf16hi(ma)));
            uint32_t ob = pack_bf16(fmaf(U[1], R[1], bf16lo(mbv)), fmaf(U[3], R[3], bf16hi(mbv)));
            unsigned char* ob8 = reinterpret_cast<unsigned char*>(p.out);
            if (va) *reinterpret_cast<uint32_t*>(ob8 + moff) = oa;
            if (vb) *reinterpret_cast<uint32_t*>(ob8 + moff + 32) = ob;
        }
    }
}

}

extern "C" void kernel_launch(void* const* d_in, const int* in_sizes, int n_in,
                              void* d_out, int out_size) {
    Params p;
    p.m = (const __nv_bfloat16*)d_in[0];
    p.idx_in = (const int*)d_in[1];
    p.idx_out = (const int*)d_in[2];
    p.dist = (const __nv_bfloat16*)d_in[3];
    p.angle = (const __nv_bfloat16*)d_in[4];
    p.centers = (const __nv_bfloat16*)d_in[5];
    p.ang_freq = (const __nv_bfloat16*)d_in[6];
    p.w_rbf = (const __nv_bfloat16*)d_in[7];
    p.w_sbf = (const __nv_bfloat16*)d_in[8];
    p.w_down = (const __nv_bfloat16*)d_in[9];
    p.w_up = (const __nv_bfloat16*)d_in[10];
    p.out = (__nv_bfloat16*)d_out;
    p.E = in_sizes[3];
    p.T = in_sizes[1];
    p.nbins = (p.E + NB - 1) / NB;

    const int smem1 = P_STAGE * 8 + (BINS_PAD + 4) * 4;
    const int smem2 = SM_TOTAL;
    static int nsm = 0;
    if (!nsm) {
        cudaFuncSetAttribute(k_partition, cudaFuncAttributeMaxDynamicSharedMemorySize, smem1);
        cudaFuncSetAttribute(k_gather, cudaFuncAttributeMaxDynamicSharedMemorySize, smem2);
        int dev = 0;
        cudaGetDevice(&dev);
        cudaDeviceGetAttribute(&nsm, cudaDevAttrMultiProcessorCount, dev);
    }
    p.nsm = nsm;
    long long per_sm = ((long long)p.T + nsm - 1) / nsm;
    int k = (int)((per_sm + P_TILE_MAX - 1) / P_TILE_MAX);
    if (k < 1) k = 1;
    long long tile = ((long long)p.T + (long long)k * nsm - 1) / ((long long)k * nsm);
    tile = (tile + 15) & ~15LL;
    if (tile > P_TILE_MAX) tile = P_TILE_MAX;
    if (tile < 16) tile = 16;
    p.tile = (int)tile;
    p.ntiles = (int)(((long long)p.T + tile - 1) / tile);
    int g1 = p.ntiles < nsm ? p.ntiles : nsm;
    if (g1 < 1) g1 = 1;
    k_partition<<<g1, P_NT, smem1>>>(p);
    k_gather<<<p.nbins, G_NT, smem2>>>(p);
}
```

```cpp
#include <cuda_runtime.h>
#include <cuda_bf16.h>
#include <stdint.h>

namespace {

constexpr int DE = 16;
constexpr int NR = 8;
constexpr int NL = 3;

constexpr int NB_LOG = 8;
constexpr int NB = 1 << NB_LOG;
constexpr int MAX_E = 400000;
constexpr int MAX_BINS = (MAX_E + NB - 1) / NB;
constexpr int BINS_PAD = 2048;
constexpr int CAPG = 5120;

constexpr int P_NT = 1024;
constexpr int P_PER = 16;
constexpr int P_TILE_MAX = P_NT * P_PER;
constexpr int P_STAGE = P_TILE_MAX + 3 * MAX_BINS + 16;

#define CFG_G_NT 256
#define CFG_G_BLOCKS 3
#define CFG_G_STAGES 2
#define CFG_P_PREFETCH 0
#define CFG_STAGGER_NS 0
#define CFG_PREFETCH 0
constexpr int G_NT = CFG_G_NT;
constexpr int G_BLOCKS = CFG_G_BLOCKS;
constexpr int G_PER = CAPG / G_NT;
constexpr int NGRP = NB / 8;
constexpr int CAPS = 5120;
constexpr int G_STAGES = CFG_G_STAGES;

__device__ uint2 g_records[(size_t)MAX_BINS * CAPG];
__device__ int g_cursor[BINS_PAD];
__device__ uint4 g_frag[4 * 32];
__device__ float g_ovf[(size_t)MAX_BINS * NB * DE];

__device__ __forceinline__ float bf16r(float x) { return __bfloat162float(__float2bfloat16_rn(x)); }
__device__ __forceinline__ float bf16lo(uint32_t v) { return __uint_as_float(v << 16); }
__device__ __forceinline__ float bf16hi(uint32_t v) { return __uint_as_float(v & 0xffff0000u); }
__device__ __forceinline__ float ldbf(const __nv_bfloat16* p) { return __bfloat162float(*p); }
__device__ __forceinline__ uint32_t smem_u32(const void* p) { return (uint32_t)__cvta_generic_to_shared(p); }

__device__ __forceinline__ uint32_t pack_bf16(float lo, float hi) {
    __nv_bfloat162 v = __floats2bfloat162_rn(lo, hi);
    return *reinterpret_cast<uint32_t*>(&v);
}
__device__ __forceinline__ uint32_t mul_bf16x2(uint32_t a, uint32_t b) {
    __nv_bfloat162 r = __hmul2(*reinterpret_cast<__nv_bfloat162*>(&a), *reinterpret_cast<__nv_bfloat162*>(&b));
    return *reinterpret_cast<uint32_t*>(&r);
}
__device__ __forceinline__ uint32_t sub_bf16x2(uint32_t a, uint32_t b) {
    __nv_bfloat162 r = __hsub2(*reinterpret_cast<__nv_bfloat162*>(&a), *reinterpret_cast<__nv_bfloat162*>(&b));
    return *reinterpret_cast<uint32_t*>(&r);
}
__device__ __forceinline__ uint32_t cos_fast_bf16x2(uint32_t x) {
    return pack_bf16(__cosf(bf16lo(x)), __cosf(bf16hi(x)));
}
__device__ __noinline__ uint32_t cos_slow_bf16x2(uint32_t x) {
    return pack_bf16(cosf(bf16lo(x)), cosf(bf16hi(x)));
}
__device__ __forceinline__ uint32_t rbf_bf16x2(uint32_t dd, uint32_t cc) {
    uint32_t t = sub_bf16x2(dd, cc);
    t = mul_bf16x2(t, t);
    t = mul_bf16x2(t, 0xC120C120u);
    return pack_bf16(__expf(bf16lo(t)), __expf(bf16hi(t)));
}

__device__ __forceinline__ void mma16816(float* d, const uint32_t* a, uint32_t b0, uint32_t b1) {
    asm volatile("mma.sync.aligned.m16n8k16.row.col.f32.bf16.bf16.f32 {%0,%1,%2,%3}, {%4,%5,%6,%7}, {%8,%9}, {%0,%1,%2,%3};"
                 : "+f"(d[0]), "+f"(d[1]), "+f"(d[2]), "+f"(d[3])
                 : "r"(a[0]), "r"(a[1]), "r"(a[2]), "r"(a[3]), "r"(b0), "r"(b1));
}
__device__ __forceinline__ void mma1688(float* d, const uint32_t* a, uint32_t b) {
    asm volatile("mma.sync.aligned.m16n8k8.row.col.f32.bf16.bf16.f32 {%0,%1,%2,%3}, {%4,%5}, {%6}, {%0,%1,%2,%3};"
                 : "+f"(d[0]), "+f"(d[1]), "+f"(d[2]), "+f"(d[3])
                 : "r"(a[0]), "r"(a[1]), "r"(b));
}
__device__ __forceinline__ uint32_t movm(uint32_t a) {
    uint32_t d;
    asm volatile("movmatrix.sync.aligned.m8n8.trans.b16 %0, %1;" : "=r"(d) : "r"(a));
    return d;
}
__device__ __forceinline__ uint32_t prmt(uint32_t a, uint32_t b, uint32_t sel) {
    uint32_t d;
    asm("prmt.b32 %0, %1, %2, %3;" : "=r"(d) : "r"(a), "r"(b), "r"(sel));
    return d;
}
__device__ __forceinline__ void ldsm_x4_trans(uint32_t* r, uint32_t addr) {
    asm volatile("ldmatrix.sync.aligned.m8n8.x4.trans.shared.b16 {%0,%1,%2,%3}, [%4];"
                 : "=r"(r[0]), "=r"(r[1]), "=r"(r[2]), "=r"(r[3]) : "r"(addr) : "memory");
}
__device__ __forceinline__ void cp_async_row(uint32_t dst, const unsigned char* base, uint32_t w) {
    uint64_t addr;
    asm("mad.wide.u32 %0, %1, 1, %2;" : "=l"(addr) : "r"(w & 0xffffffu), "l"(base));
    asm volatile("{ .reg .pred p; setp.gt.u32 p, %2, 0xffffff; @p cp.async.cg.shared.global [%0], [%1], 16; }" :: "r"(dst), "l"(addr), "r"(w) : "memory");
}
__device__ __forceinline__ void cp_async_commit() { asm volatile("cp.async.commit_group;" ::: "memory"); }
template <int N> __device__ __forceinline__ void cp_async_wait() { asm volatile("cp.async.wait_group %0;" :: "n"(N) : "memory"); }

struct Params {
    const __nv_bfloat16* m;
    const int* idx_in;
    const int* idx_out;
    const __nv_bfloat16* dist;
    const __nv_bfloat16* angle;
    const __nv_bfloat16* centers;
    const __nv_bfloat16* ang_freq;
    const __nv_bfloat16* w_rbf;
    const __nv_bfloat16* w_sbf;
    const __nv_bfloat16* w_down;
    const __nv_bfloat16* w_up;
    __nv_bfloat16* out;
    int E, T, nbins, ntiles, tile, nsm;
};

__device__ __noinline__ void slow_bin(const Params* pp, int bin, int tid, int nthreads) {
    const Params& p = *pp;
    for (int t = tid; t < p.T; t += nthreads) {
        const int out = p.idx_out[t];
        if ((out >> NB_LOG) != bin) continue;
        const int in = p.idx_in[t];
        const float ang = ldbf(p.angle + t);
        float mrow[DE], rb[NR], cb[NL];
        for (int k = 0; k < DE; k++) mrow[k] = ldbf(p.m + (size_t)in * DE + k);
        float d = ldbf(p.dist + out);
        for (int r = 0; r < NR; r++) {
            float u = bf16r(d - ldbf(p.centers + r));
            u = bf16r(u * u);
            u = bf16r(-10.0f * u);
            rb[r] = bf16r(__expf(u));
        }
        for (int l = 0; l < NL; l++) cb[l] = bf16r(cosf(bf16r(ldbf(p.ang_freq + l) * ang)));
        for (int c = 0; c < DE; c++) {
            float md = 0.f, s = 0.f;
            for (int k = 0; k < DE; k++) md = fmaf(mrow[k], ldbf(p.w_down + k * DE + c), md);
            for (int r = 0; r < NR; r++)
                for (int l = 0; l < NL; l++) s = fmaf(rb[r] * cb[l], ldbf(p.w_sbf + (r * NL + l) * DE + c), s);
            atomicAdd(&g_ovf[(size_t)out * DE + c], md * s);
        }
    }
    __threadfence();
}

__device__ __forceinline__ int4 ld4_guard(const int* p, int i, int n, int fill) {
    if (i + 3 < n) return __ldcs(reinterpret_cast<const int4*>(p + i));
    int4 r;
    r.x = (i + 0 < n) ? p[i + 0] : fill;
    r.y = (i + 1 < n) ? p[i + 1] : fill;
    r.z = (i + 2 < n) ? p[i + 2] : fill;
    r.w = fill;
    return r;
}
__device__ __forceinline__ uint2 ld4h_guard(const unsigned short* p, int i, int n) {
    if (i + 3 < n) return __ldcs(reinterpret_cast<const uint2*>(p + i));
    uint32_t a = (i + 0 < n) ? p[i + 0] : 0u, b = (i + 1 < n) ? p[i + 1] : 0u, c = (i + 2 < n) ? p[i + 2] : 0u;
    return make_uint2(a | (b << 16), c);
}

__device__ __forceinline__ void prefetch_tile(const Params& p, int tile, int which) {
    const int base = tile * p.tile;
    const int n = min(p.tile, p.T - base) & ~7;
    if (n <= 0) return;
    if (which == 0) asm volatile("cp.async.bulk.prefetch.L2.global [%0], %1;" :: "l"(p.idx_out + base), "r"(n * 4) : "memory");
    if (which == 1) asm volatile("cp.async.bulk.prefetch.L2.global [%0], %1;" :: "l"(p.idx_in + base), "r"(n * 4) : "memory");
    if (which == 2) asm volatile("cp.async.bulk.prefetch.L2.global [%0], %1;" :: "l"(p.angle + base), "r"(n * 2) : "memory");
}

__global__ void __launch_bounds__(P_NT, 1) k_partition(const __grid_constant__ Params p) {
    extern __shared__ __align__(16) unsigned char smem_raw[];
    uint2* stage = reinterpret_cast<uint2*>(smem_raw);
    int* hist = reinterpret_cast<int*>(smem_raw + (size_t)P_STAGE * 8);
    __shared__ int warp_sums[P_NT / 32];
    static_assert(BINS_PAD == 2 * P_NT, "two bins per thread in the scan");

    const int tid = threadIdx.x;
    const int lane = tid & 31, wid = tid >> 5;
    const unsigned short* ang16 = reinterpret_cast<const unsigned short*>(p.angle);

    if (blockIdx.x == 0 && wid == P_NT / 32 - 1) {
        const int g = lane >> 2, q = lane & 3;
        const unsigned short* wd = reinterpret_cast<const unsigned short*>(p.w_down);
        const unsigned short* wu = reinterpret_cast<const unsigned short*>(p.w_up);
        const unsigned short* ws = reinterpret_cast<const unsigned short*>(p.w_sbf);
        const unsigned short* wr = reinterpret_cast<const unsigned short*>(p.w_rbf);
        uint4 t;
        t.x = (uint32_t)wd[(2 * q) * DE + g] | ((uint32_t)wd[(2 * q + 1) * DE + g] << 16);
        t.y = (uint32_t)wd[(2 * q) * DE + g + 8] | ((uint32_t)wd[(2 * q + 1) * DE + g + 8] << 16);
        t.z = (uint32_t)wd[(2 * q + 8) * DE + g] | ((uint32_t)wd[(2 * q + 9) * DE + g] << 16);
        t.w = (uint32_t)wd[(2 * q + 8) * DE + g + 8] | ((uint32_t)wd[(2 * q + 9) * DE + g + 8] << 16);
        g_frag[lane] = t;
        const int cA = 2 * g, cB = 2 * g + 1;
        t.x = (uint32_t)wu[(2 * q) * DE + cA] | ((uint32_t)wu[(2 * q + 1) * DE + cA] << 16);
        t.y = (uint32_t)wu[(2 * q) * DE + cB] | ((uint32_t)wu[(2 * q + 1) * DE + cB] << 16);
        t.z = (uint32_t)wu[(2 * q + 8) * DE + cA] | ((uint32_t)wu[(2 * q + 9) * DE + cA] << 16);
        t.w = (uint32_t)wu[(2 * q + 8) * DE + cB] | ((uint32_t)wu[(2 * q + 9) * DE + cB] << 16);
        g_frag[32 + lane] = t;
        uint32_t sb[NL][2];
#pragma unroll
        for (int l = 0; l < NL; l++) {
            sb[l][0] = (uint32_t)ws[((2 * q) * NL + l) * DE + g] | ((uint32_t)ws[((2 * q + 1) * NL + l) * DE + g] << 16);
            sb[l][1] = (uint32_t)ws[((2 * q) * NL + l) * DE + g + 8] | ((uint32_t)ws[((2 * q + 1) * NL + l) * DE + g + 8] << 16);
        }
        g_frag[64 + lane] = make_uint4(sb[0][0], sb[0][1], sb[1][0], sb[1][1]);
        t.x = sb[2][0]; t.y = sb[2][1];
        t.z = (uint32_t)wr[(2 * q) * DE + cA] | ((uint32_t)wr[(2 * q + 1) * DE + cA] << 16);
        t.w = (uint32_t)wr[(2 * q) * DE + cB] | ((uint32_t)wr[(2 * q + 1) * DE + cB] << 16);
        g_frag[96 + lane] = t;
    }

    int4 O[P_PER / 4];
    int tile = blockIdx.x;
    if (tile < p.ntiles) {
        const int base = tile * p.tile, n = min(p.tile, p.T - base);
#pragma unroll
        for (int v = 0; v < P_PER / 4; v++) O[v] = ld4_guard(p.idx_out + base, (v * P_NT + tid) * 4, n, -1);
    }
    reinterpret_cast<int2*>(hist)[tid] = make_int2(0, 0);
    if (tid == 0) hist[BINS_PAD] = 0;
    for (; tile < p.ntiles; tile += gridDim.x) {
        const int base = tile * p.tile, n = min(p.tile, p.T - base);
        __syncthreads();
#pragma unroll
        for (int v = 0; v < P_PER / 4; v++) {
            atomicAdd(&hist[min((uint32_t)O[v].x >> NB_LOG, (uint32_t)BINS_PAD)], 1);
            atomicAdd(&hist[min((uint32_t)O[v].y >> NB_LOG, (uint32_t)BINS_PAD)], 1);
            atomicAdd(&hist[min((uint32_t)O[v].z >> NB_LOG, (uint32_t)BINS_PAD)], 1);
            atomicAdd(&hist[min((uint32_t)O[v].w >> NB_LOG, (uint32_t)BINS_PAD)], 1);
        }
        int4 I[P_PER / 4];
        uint2 A[P_PER / 4];
#pragma unroll
        for (int v = 0; v < P_PER / 4; v++) {
            I[v] = ld4_guard(p.idx_in + base, (v * P_NT + tid) * 4, n, 0);
            A[v] = ld4h_guard(ang16 + base, (v * P_NT + tid) * 4, n);
        }
        __syncthreads();
        const int2 c2 = reinterpret_cast<int2*>(hist)[tid];
        const int pc0 = (c2.x + 3) & ~3, pc1 = (c2.y + 3) & ~3;
        int g0 = 0, g1 = 0;
        if (pc0) g0 = atomicAdd(&g_cursor[2 * tid], pc0);
        if (pc1) g1 = atomicAdd(&g_cursor[2 * tid + 1], pc1);
        const int s = pc0 + pc1;
        int inc = s;
#pragma unroll
        for (int o = 1; o < 32; o <<= 1) {
            int t = __shfl_up_sync(0xffffffffu, inc, o);
            if (lane >= o) inc += t;
        }
        if (lane == 31) warp_sums[wid] = inc;
        asm volatile("cp.async.bulk.wait_group.read 0;" ::: "memory");
        __syncthreads();
        int woff;
        {
            int ws = warp_sums[lane];
            int winc = ws;
#pragma unroll
            for (int o = 1; o < 32; o <<= 1) {
                int t = __shfl_up_sync(0xffffffffu, winc, o);
                if (lane >= o) winc += t;
            }
            woff = __shfl_sync(0xffffffffu, winc - ws, wid);
        }
        const int e0 = woff + inc - s, e1 = e0 + pc0;
        reinterpret_cast<int2*>(hist)[tid] = make_int2(e0, e1);
        if (tid == 0) hist[BINS_PAD] = P_STAGE;
        for (int k = c2.x; k < pc0; k++) stage[e0 + k] = make_uint2(0u, 0xffffffffu);
        for (int k = c2.y; k < pc1; k++) stage[e1 + k] = make_uint2(0u, 0xffffffffu);
        __syncthreads();
#pragma unroll
        for (int v = 0; v < P_PER / 4; v++) {
            const uint32_t o[4] = {(uint32_t)O[v].x, (uint32_t)O[v].y, (uint32_t)O[v].z, (uint32_t)O[v].w};
            const uint32_t in[4] = {(uint32_t)I[v].x, (uint32_t)I[v].y, (uint32_t)I[v].z, (uint32_t)I[v].w};
            const uint32_t an[4] = {A[v].x & 0xffffu, A[v].x >> 16, A[v].y & 0xffffu, A[v].y >> 16};
#pragma unroll
            for (int u = 0; u < 4; u++) {
                int pos = atomicAdd(&hist[min(o[u] >> NB_LOG, (uint32_t)BINS_PAD)], 1);
                stage[min(pos, P_STAGE - 1)] = make_uint2((in[u] << 5) | (0x1000000u << (o[u] & 7)), an[u] | ((o[u] & 255u) << 16));
            }
        }
        {
            const int nt = tile + gridDim.x;
            if (nt < p.ntiles) {
                const int nbase = nt * p.tile, nn = min(p.tile, p.T - nbase);
#pragma unroll
                for (int v = 0; v < P_PER / 4; v++) O[v] = ld4_guard(p.idx_out + nbase, (v * P_NT + tid) * 4, nn, -1);
            }
        }
        asm volatile("fence.proxy.async.shared::cta;" ::: "memory");
        __syncthreads();
        if (pc0 && g0 + pc0 <= CAPG)
            asm volatile("cp.async.bulk.global.shared::cta.bulk_group [%0], [%1], %2;"
                         :: "l"(g_records + (size_t)(2 * tid) * CAPG + g0), "r"(smem_u32(stage + e0)), "r"(pc0 * 8) : "memory");
        if (pc1 && g1 + pc1 <= CAPG)
            asm volatile("cp.async.bulk.global.shared::cta.bulk_group [%0], [%1], %2;"
                         :: "l"(g_records + (size_t)(2 * tid + 1) * CAPG + g1), "r"(smem_u32(stage + e1)), "r"(pc1 * 8) : "memory");
        asm volatile("cp.async.bulk.commit_group;" ::: "memory");
        reinterpret_cast<int2*>(hist)[tid] = make_int2(0, 0);
        if (tid == 0) hist[BINS_PAD] = 0;
    }
    asm volatile("cp.async.bulk.wait_group 0;" ::: "memory");
}

constexpr int S_NT = 256;
constexpr int T_NT = 256;
constexpr int NTEAM = 2;
constexpr int NBUF = 3;
constexpr int K2_NT = S_NT + NTEAM * T_NT;
constexpr int S_PER = CAPG / S_NT;
constexpr int NOCT = CAPS / 8;
constexpr int SM_IDX = 0;
constexpr int SM_CA = SM_IDX + (CAPS + 32) * 4;
constexpr int SM_CB = SM_CA + NOCT * 16;
constexpr int SM_C2 = SM_CB + NOCT * 16;
constexpr int SM_OH = SM_C2 + (NOCT + 4) * 16;
constexpr int SM_GS = SM_OH + (NOCT + 8) * 8;
constexpr int SM_BUF = SM_GS + 256;
constexpr int SM_RING = NBUF * SM_BUF;
constexpr int SM_TOTAL = SM_RING + (NTEAM * T_NT / 32) * G_STAGES * 1024;
static_assert(SM_BUF % 128 == 0, "buffer alignment");
constexpr int BAR_FULL = 1, BAR_EMPTY = 1 + NBUF, BAR_SORT = 1 + 2 * NBUF;

__device__ __forceinline__ uint2 lds64(uint32_t a) { uint2 v; asm volatile("ld.shared.v2.u32 {%0,%1}, [%2];" : "=r"(v.x), "=r"(v.y) : "r"(a) : "memory"); return v; }
__device__ __forceinline__ void bar_sync(int id, int n) { asm volatile("bar.sync %0, %1;" :: "r"(id), "r"(n) : "memory"); }
__device__ __forceinline__ void bar_arrive(int id, int n) { asm volatile("bar.arrive %0, %1;" :: "r"(id), "r"(n) : "memory"); }

__device__ __forceinline__ void load_records(uint4* r, int bin, int n, int tid) {
    const uint4* rec = reinterpret_cast<const uint4*>(g_records + (size_t)bin * CAPG) + tid;
#pragma unroll
    for (int j = 0; j < S_PER / 2; j++) {
        r[j] = make_uint4(0u, 0xffffffffu, 0u, 0xffffffffu);
        if ((j * S_NT + tid) * 2 < n) r[j] = __ldcs(rec + j * S_NT);
    }
}

__global__ void __launch_bounds__(K2_NT, 1) k_gather(const __grid_constant__ Params p) {
    extern __shared__ __align__(128) unsigned char smem_raw[];
    __shared__ int cnts[NB + 32];
    __shared__ int warp_sums[NB / 32];

    const int lane = threadIdx.x & 31;
    const int nmine = (p.nbins - (int)blockIdx.x + (int)gridDim.x - 1) / (int)gridDim.x;

    if (threadIdx.x < S_NT) {
        const int tid = threadIdx.x, wid = tid >> 5;
        const unsigned short* fq = reinterpret_cast<const unsigned short*>(p.ang_freq);
        const uint32_t f0 = (uint32_t)fq[0] * 0x10001u, f1 = (uint32_t)fq[1] * 0x10001u, f2 = (uint32_t)fq[2] * 0x10001u;
        const uint32_t fmaxp = max(max(f0 & 0x7fff7fffu, f1 & 0x7fff7fffu), f2 & 0x7fff7fffu);
        const uint32_t dkey = NB + lane;
        uint4 r[S_PER / 2];
        int total = 0;
        if (nmine > 0) {
            total = g_cursor[blockIdx.x];
            load_records(r, blockIdx.x, total > CAPG ? 0 : total, tid);
        }
        cnts[tid] = 0;
        int buf = 0;
#pragma unroll 1
        for (int k = 0; k < nmine; k++) {
            const int bin = blockIdx.x + k * gridDim.x;
            bool ovf = total > CAPG;
            unsigned char* sb = smem_raw + buf * SM_BUF;
            uint32_t* sidx = reinterpret_cast<uint32_t*>(sb + SM_IDX);
            unsigned short* sang = reinterpret_cast<unsigned short*>(sb + SM_C2);
            int* gstart = reinterpret_cast<int*>(sb + SM_GS);
            bar_sync(BAR_SORT, S_NT);
            if (tid == 0) g_cursor[bin] = 0;
#pragma unroll
            for (int j = 0; j < S_PER / 2; j++) {
                atomicAdd(&cnts[min(r[j].y >> 16, dkey)], 1);
                atomicAdd(&cnts[min(r[j].w >> 16, dkey)], 1);
            }
            bar_sync(BAR_SORT, S_NT);
            const int c = cnts[tid];
            int gt = c;
            gt += __shfl_xor_sync(0xffffffffu, gt, 1);
            gt += __shfl_xor_sync(0xffffffffu, gt, 2);
            gt += __shfl_xor_sync(0xffffffffu, gt, 4);
            const int npad = ((gt + 31) & ~31) - gt;
            const int cp = c + (((lane & 7) == 7) ? npad : 0);
            int inc = cp;
#pragma unroll
            for (int o = 1; o < 32; o <<= 1) {
                int t = __shfl_up_sync(0xffffffffu, inc, o);
                if (lane >= o) inc += t;
            }
            if (lane == 31) warp_sums[wid] = inc;
            if (k >= NBUF) bar_sync(BAR_EMPTY + buf, S_NT + T_NT);
            bar_sync(BAR_SORT, S_NT);
            {
                int woff = 0, tot = 0;
#pragma unroll
                for (int w = 0; w < NB / 32; w++) { woff += (w < wid) ? warp_sums[w] : 0; tot += warp_sums[w]; }
                ovf = ovf || (tot > CAPS);
                const int st = ovf ? 0 : woff + inc - cp;
                cnts[tid] = ovf ? CAPS : st;
                if ((lane & 7) == 0) gstart[tid >> 3] = st;
                if (tid == NB - 1) { gstart[NGRP] = ovf ? 0 : tot; gstart[NGRP + 1] = ovf ? 1 : 0; }
                if (tid < 32) cnts[NB + tid] = CAPS;
                const int gend = __shfl_sync(0xffffffffu, woff + inc, lane | 7);
                if (!ovf) {
#pragma unroll
                    for (int kk0 = 0; kk0 < 4; kk0++) {
                        const int kk = (lane & 7) + 8 * kk0;
                        if (kk < npad) { sidx[gend - 1 - kk] = 0u; sang[gend - 1 - kk] = 0; }
                    }
                }
            }
            bar_sync(BAR_SORT, S_NT);
#pragma unroll
            for (int j = 0; j < S_PER / 2; j++) {
                {
                    const int pos = min(atomicAdd(&cnts[min(r[j].y >> 16, dkey)], 1), CAPS);
                    sidx[pos] = r[j].x;
                    sang[pos] = (unsigned short)r[j].y;
                }
                {
                    const int pos = min(atomicAdd(&cnts[min(r[j].w >> 16, dkey)], 1), CAPS);
                    sidx[pos] = r[j].z;
                    sang[pos] = (unsigned short)r[j].w;
                }
            }
            if (ovf) slow_bin(&p, bin, tid, S_NT);
            if (k + 1 < nmine) {
                total = g_cursor[bin + gridDim.x];
                load_records(r, bin + gridDim.x, total > CAPG ? 0 : total, tid);
            }
            bar_sync(BAR_SORT, S_NT);
            cnts[tid] = 0;
            {
                uint4* scA = reinterpret_cast<uint4*>(sb + SM_CA);
                uint4* scB = reinterpret_cast<uint4*>(sb + SM_CB);
                uint2* soh = reinterpret_cast<uint2*>(sb + SM_OH);
                const int noct = gstart[NGRP] >> 3;
                for (int i = tid; i < noct; i += S_NT) {
                    const uint4 an = reinterpret_cast<const uint4*>(sang)[i];
                    const uint4 w0 = reinterpret_cast<const uint4*>(sidx)[2 * i];
                    const uint4 w1 = reinterpret_cast<const uint4*>(sidx)[2 * i + 1];
                    soh[i] = make_uint2(prmt(prmt(w0.x, w0.z, 0x0073), prmt(w1.x, w1.z, 0x0073), 0x5410),
                                        prmt(prmt(w0.y, w0.w, 0x0073), prmt(w1.y, w1.w, 0x0073), 0x5410));
                    const uint32_t aA0 = prmt(an.x, an.y, 0x5410), aA1 = prmt(an.z, an.w, 0x5410);
                    const uint32_t aB0 = prmt(an.x, an.y, 0x7632), aB1 = prmt(an.z, an.w, 0x7632);
                    const uint32_t amax = __vmaxu2(__vmaxu2(an.x & 0x7fff7fffu, an.y & 0x7fff7fffu), __vmaxu2(an.z & 0x7fff7fffu, an.w & 0x7fff7fffu));
                    const uint32_t t = mul_bf16x2(amax, fmaxp);
                    uint4 oA, oB, o2;
                    if ((t >> 16) < 0x4300u && (t & 0xffffu) < 0x4300u) {
                        oA.x = cos_fast_bf16x2(mul_bf16x2(aA0, f0)); oA.y = cos_fast_bf16x2(mul_bf16x2(aA1, f0));
                        oA.z = cos_fast_bf16x2(mul_bf16x2(aA0, f1)); oA.w = cos_fast_bf16x2(mul_bf16x2(aA1, f1));
                        oB.x = cos_fast_bf16x2(mul_bf16x2(aB0, f0)); oB.y = cos_fast_bf16x2(mul_bf16x2(aB1, f0));
                        oB.z = cos_fast_bf16x2(mul_bf16x2(aB0, f1)); oB.w = cos_fast_bf16x2(mul_bf16x2(aB1, f1));
                        o2.x = cos_fast_bf16x2(mul_bf16x2(aA0, f2)); o2.y = cos_fast_bf16x2(mul_bf16x2(aA1, f2));
                        o2.z = cos_fast_bf16x2(mul_bf16x2(aB0, f2)); o2.w = cos_fast_bf16x2(mul_bf16x2(aB1, f2));
                    } else {
                        oA.x = cos_slow_bf16x2(mul_bf16x2(aA0, f0)); oA.y = cos_slow_bf16x2(mul_bf16x2(aA1, f0));
                        oA.z = cos_slow_bf16x2(mul_bf16x2(aA0, f1)); oA.w = cos_slow_bf16x2(mul_bf16x2(aA1, f1));
                        oB.x = cos_slow_bf16x2(mul_bf16x2(aB0, f0)); oB.y = cos_slow_bf16x2(mul_bf16x2(aB1, f0));
                        oB.z = cos_slow_bf16x2(mul_bf16x2(aB0, f1)); oB.w = cos_slow_bf16x2(mul_bf16x2(aB1, f1));
                        o2.x = cos_slow_bf16x2(mul_bf16x2(aA0, f2)); o2.y = cos_slow_bf16x2(mul_bf16x2(aA1, f2));
                        o2.z = cos_slow_bf16x2(mul_bf16x2(aB0, f2)); o2.w = cos_slow_bf16x2(mul_bf16x2(aB1, f2));
                    }
                    scA[i] = oA;
                    scB[i] = oB;
                    reinterpret_cast<uint4*>(sang)[i] = o2;
                }
            }
            bar_arrive(BAR_FULL + buf, S_NT + T_NT);
            buf = (buf == NBUF - 1) ? 0 : buf + 1;
        }
    } else {
        const int gtid = threadIdx.x - S_NT;
        const int team = gtid / T_NT, wid = (gtid % T_NT) >> 5;
        const int g = lane >> 2, q = lane & 3;
        constexpr int GPW = NGRP / (T_NT / 32);
        const int grp0 = wid * GPW;
        const unsigned char* mb = reinterpret_cast<const unsigned char*>(p.m);
        const uint32_t smem0 = smem_u32(smem_raw);

        const uint32_t ring = smem0 + SM_RING + (gtid >> 5) * (G_STAGES * 1024);
        const int cj = lane >> 1;
        const int crow = (cj >> 2) * 2 + (cj & 1) + ((cj >> 1) & 1) * 8;
        const uint32_t cdst = ring + (uint32_t)(crow * 32 + (((lane ^ (crow >> 2)) & 1) * 16));
        const unsigned char* msrc = mb + (lane & 1) * 16;
        const int lrow = (lane >> 4) * 8 + (lane & 7);
        const uint32_t lsrc = ring + (uint32_t)(lrow * 32 + ((((lane >> 3) ^ (lrow >> 2)) & 1) * 16));
        const uint32_t cen = reinterpret_cast<const uint32_t*>(p.centers)[q];
        for (int i = lane; i < G_STAGES * 64; i += 32)
            reinterpret_cast<uint4*>(smem_raw + SM_RING + (gtid >> 5) * (G_STAGES * 1024))[i] = make_uint4(0u, 0u, 0u, 0u);
        __syncwarp();
        uint4 cA = make_uint4(0u, 0u, 0u, 0u), cB = cA, c2 = cA;

#pragma unroll 1
        for (int k = team; k < nmine; k += NTEAM) {
            const int bin = blockIdx.x + k * gridDim.x;
            const int buf = k % NBUF;
            const uint32_t sbase = smem0 + buf * SM_BUF;
            const int* gstart = reinterpret_cast<const int*>(smem_raw + buf * SM_BUF + SM_GS);
            const int ew = bin * NB + grp0 * 8;
            const unsigned short* pdist = reinterpret_cast<const unsigned short*>(p.dist) + ew + g;
            const uint32_t moff0 = (uint32_t)(ew + 2 * q) * 32u + 4u * g;
            const int nleft = p.E - ew;
            uint32_t dgn = (g < nleft) ? (uint32_t)pdist[0] : 0u;
            uint32_t man = (2 * q < nleft) ? __ldg(reinterpret_cast<const uint32_t*>(mb + moff0)) : 0u;
            uint32_t mbn = (2 * q + 1 < nleft) ? __ldg(reinterpret_cast<const uint32_t*>(mb + moff0 + 32)) : 0u;

            bar_sync(BAR_FULL + buf, S_NT + T_NT);
            const bool ovf = gstart[NGRP + 1] != 0;
            const int wbeg = gstart[grp0], wend = gstart[grp0 + GPW];
            uint32_t iaddr = sbase + SM_IDX + (wbeg + 2 * cj) * 4;
            const uint32_t iend = sbase + SM_IDX + wend * 4;
            uint32_t ioff = 0;
#pragma unroll
            for (int s = 0; s < G_STAGES - 1; s++) {
                if (iaddr < iend) {
                    const uint2 w = lds64(iaddr);
                    cp_async_row(cdst + ioff, msrc, w.x);
                    cp_async_row(cdst + ioff + 512, msrc, w.y);
                }
                cp_async_commit();
                iaddr += 128; ioff += 1024;
            }
            uint2 wnext = make_uint2(0u, 0u);
            if (iaddr < iend) wnext = lds64(iaddr);
            uint32_t ac = sbase + SM_CA + ((wbeg >> 3) + q) * 16;
            uint32_t aoh = sbase + SM_OH + ((wbeg >> 3) + q) * 8;
            uint2 ohnext = lds64(aoh);
#pragma unroll 1
            for (int gi = 0; gi < GPW; gi++) {
                const uint32_t aend = sbase + SM_OH + (uint32_t)gstart[grp0 + gi + 1];
                const uint32_t moff = moff0 + gi * 256;
                const bool va = gi * 8 + 2 * q < nleft, vb = gi * 8 + 2 * q + 1 < nleft;
                const uint32_t dg = dgn, ma = man, mbv = mbn;
                if (gi + 1 < GPW) {
                    dgn = (gi * 8 + 8 + g < nleft) ? (uint32_t)pdist[gi * 8 + 8] : 0u;
                    man = (gi * 8 + 8 + 2 * q < nleft) ? __ldg(reinterpret_cast<const uint32_t*>(mb + moff + 256)) : 0u;
                    mbn = (gi * 8 + 9 + 2 * q < nleft) ? __ldg(reinterpret_cast<const uint32_t*>(mb + moff + 288)) : 0u;
                }

                float D[NL][4];
#pragma unroll
                for (int l = 0; l < NL; l++)
#pragma unroll
                    for (int c4 = 0; c4 < 4; c4++) D[l][c4] = 0.f;
#pragma unroll 1
                while (aoh < aend) {
                    cp_async_row(cdst + ioff, msrc, wnext.x);
                    cp_async_row(cdst + ioff + 512, msrc, wnext.y);
                    cp_async_commit();
                    iaddr += 128; ioff = (ioff == (G_STAGES - 1) * 1024) ? 0 : ioff + 1024;
                    wnext = make_uint2(0u, 0u);
                    if (iaddr < iend) wnext = lds64(iaddr);
                    const uint32_t kA = (ohnext.x >> g) & 0x01010101u, kB = (ohnext.y >> g) & 0x01010101u;
                    asm volatile("{ .reg .pred pa, pb, pc; setp.ne.u32 pa, %13, 0; setp.ne.u32 pb, %14, 0; or.pred pc, pa, pb;\n\t"
                                 "@pa ld.shared.v4.u32 {%0,%1,%2,%3}, [%12];\n\t"
                                 "@pb ld.shared.v4.u32 {%4,%5,%6,%7}, [%12+%15];\n\t"
                                 "@pc ld.shared.v4.u32 {%8,%9,%10,%11}, [%12+%16]; }"
                                 : "+r"(cA.x), "+r"(cA.y), "+r"(cA.z), "+r"(cA.w), "+r"(cB.x), "+r"(cB.y), "+r"(cB.z), "+r"(cB.w),
                                   "+r"(c2.x), "+r"(c2.y), "+r"(c2.z), "+r"(c2.w)
                                 : "r"(ac), "r"(kA), "r"(kB), "n"(SM_CB - SM_CA), "n"(SM_C2 - SM_CA) : "memory");
                    ac += 64; aoh += 32;
                    ohnext = lds64(aoh);
                    const uint32_t kA0 = prmt(kA, 0, 0x4140) * 0x3F80u, kA1 = prmt(kA, 0, 0x4342) * 0x3F80u;
                    const uint32_t kB0 = prmt(kB, 0, 0x4140) * 0x3F80u, kB1 = prmt(kB, 0, 0x4342) * 0x3F80u;
                    cp_async_wait<G_STAGES - 1>();
                    __syncwarp();
                    uint32_t a[4], b[4];
                    ldsm_x4_trans(a, lsrc + ioff);
                    ldsm_x4_trans(b, lsrc + ioff + 512);
                    mma16816(D[0], a, mul_bf16x2(cA.x, kA0), mul_bf16x2(cA.y, kA1));
                    mma16816(D[1], a, mul_bf16x2(cA.z, kA0), mul_bf16x2(cA.w, kA1));
                    mma16816(D[2], a, mul_bf16x2(c2.x, kA0), mul_bf16x2(c2.y, kA1));
                    mma16816(D[0], b, mul_bf16x2(cB.x, kB0), mul_bf16x2(cB.y, kB1));
                    mma16816(D[1], b, mul_bf16x2(cB.z, kB0), mul_bf16x2(cB.w, kB1));
                    mma16816(D[2], b, mul_bf16x2(c2.z, kB0), mul_bf16x2(c2.w, kB1));
                }
                if (gi == GPW - 1 && k + NBUF < nmine) bar_arrive(BAR_EMPTY + buf, S_NT + T_NT);
                uint32_t adown[4], aup[4], asbf[NL][2], arb[2];
                {
                    const uint4* fr = reinterpret_cast<const uint4*>(g_frag) + lane;
                    uint4 t0, t1, t2, t3;
                    asm volatile("ld.global.nc.v4.u32 {%0,%1,%2,%3}, [%4];" : "=r"(t0.x), "=r"(t0.y), "=r"(t0.z), "=r"(t0.w) : "l"(fr));
                    asm volatile("ld.global.nc.v4.u32 {%0,%1,%2,%3}, [%4];" : "=r"(t2.x), "=r"(t2.y), "=r"(t2.z), "=r"(t2.w) : "l"(fr + 64));
                    asm volatile("ld.global.nc.v4.u32 {%0,%1,%2,%3}, [%4];" : "=r"(t3.x), "=r"(t3.y), "=r"(t3.z), "=r"(t3.w) : "l"(fr + 96));
                    asm volatile("ld.global.nc.v4.u32 {%0,%1,%2,%3}, [%4];" : "=r"(t1.x), "=r"(t1.y), "=r"(t1.z), "=r"(t1.w) : "l"(fr + 32));
                    adown[0] = t0.x; adown[1] = t0.y; adown[2] = t0.z; adown[3] = t0.w;
                    aup[0] = t1.x; aup[1] = t1.y; aup[2] = t1.z; aup[3] = t1.w;
                    asbf[0][0] = t2.x; asbf[0][1] = t2.y; asbf[1][0] = t2.z; asbf[1][1] = t2.w;
                    asbf[2][0] = t3.x; asbf[2][1] = t3.y; arb[0] = t3.z; arb[1] = t3.w;
                }
                const uint32_t brbf = rbf_bf16x2(dg * 0x10001u, cen);
                float agg[4] = {0.f, 0.f, 0.f, 0.f};
#pragma unroll
                for (int l = 0; l < NL; l++) {
                    const uint32_t h0 = movm(pack_bf16(D[l][0], D[l][1]));
                    const uint32_t h1 = movm(pack_bf16(D[l][2], D[l][3]));
                    float S[4] = {0.f, 0.f, 0.f, 0.f};
                    float G[4] = {0.f, 0.f, 0.f, 0.f};
                    mma16816(S, adown, h0, h1);
                    mma1688(G, asbf[l], brbf);
#pragma unroll
                    for (int c4 = 0; c4 < 4; c4++) agg[c4] = fmaf(S[c4], G[c4], agg[c4]);
                }
                if (ovf) {
                    const int ea = ew + gi * 8 + 2 * q;
                    if (va) {
                        float* pa = g_ovf + (size_t)ea * DE + g;
                        agg[0] += __ldcg(pa); agg[2] += __ldcg(pa + 8);
                        pa[0] = 0.f; pa[8] = 0.f;
                    }
                    if (vb) {
                        float* pb = g_ovf + (size_t)(ea + 1) * DE + g;
                        agg[1] += __ldcg(pb); agg[3] += __ldcg(pb + 8);
                        pb[0] = 0.f; pb[8] = 0.f;
                    }
                }
                {
                    const uint32_t h0 = movm(pack_bf16(agg[0], agg[1]));
                    const uint32_t h1 = movm(pack_bf16(agg[2], agg[3]));
                    float U[4] = {0.f, 0.f, 0.f, 0.f};
                    float R[4] = {0.f, 0.f, 0.f, 0.f};
                    mma16816(U, aup, h0, h1);
                    mma1688(R, arb, brbf);
                    uint32_t oa = pack_bf16(fmaf(U[0], R[0], bf16lo(ma)), fmaf(U[2], R[2], bf16hi(ma)));
                    uint32_t ob = pack_bf16(fmaf(U[1], R[1], bf16lo(mbv)), fmaf(U[3], R[3], bf16hi(mbv)));
                    unsigned char* ob8 = reinterpret_cast<unsigned char*>(p.out);
                    if (va) *reinterpret_cast<uint32_t*>(ob8 + moff) = oa;
                    if (vb) *reinterpret_cast<uint32_t*>(ob8 + moff + 32) = ob;
                }
            }
        }
    }
}

}

extern "C" void kernel_launch(void* const* d_in, const int* in_sizes, int n_in,
                              void* d_out, int out_size) {
    Params p;
    p.m = (const __nv_bfloat16*)d_in[0];
    p.idx_in = (const int*)d_in[1];
    p.idx_out = (const int*)d_in[2];
    p.dist = (const __nv_bfloat16*)d_in[3];
    p.angle = (const __nv_bfloat16*)d_in[4];
    p.centers = (const __nv_bfloat16*)d_in[5];
    p.ang_freq = (const __nv_bfloat16*)d_in[6];
    p.w_rbf = (const __nv_bfloat16*)d_in[7];
    p.w_sbf = (const __nv_bfloat16*)d_in[8];
    p.w_down = (const __nv_bfloat16*)d_in[9];
    p.w_up = (const __nv_bfloat16*)d_in[10];
    p.out = (__nv_bfloat16*)d_out;
    p.E = in_sizes[3];
    p.T = in_sizes[1];
    p.nbins = (p.E + NB - 1) / NB;

    const int smem1 = P_STAGE * 8 + (BINS_PAD + 4) * 4;
    const int smem2 = SM_TOTAL;
    static int nsm = 0;
    if (!nsm) {
        cudaFuncSetAttribute(k_partition, cudaFuncAttributeMaxDynamicSharedMemorySize, smem1);
        cudaFuncSetAttribute(k_gather, cudaFuncAttributeMaxDynamicSharedMemorySize, smem2);
        int dev = 0;
        cudaGetDevice(&dev);
        cudaDeviceGetAttribute(&nsm, cudaDevAttrMultiProcessorCount, dev);
    }
    p.nsm = nsm;
    long long per_sm = ((long long)p.T + nsm - 1) / nsm;
    int k = (int)((per_sm + P_TILE_MAX - 1) / P_TILE_MAX);
    if (k < 1) k = 1;
    long long tile = ((long long)p.T + (long long)k * nsm - 1) / ((long long)k * nsm);
    tile = (tile + 15) & ~15LL;
    if (tile > P_TILE_MAX) tile = P_TILE_MAX;
    if (tile < 16) tile = 16;
    p.tile = (int)tile;
    p.ntiles = (int)(((long long)p.T + tile - 1) / tile);
    int g1 = p.ntiles < nsm ? p.ntiles : nsm;
    if (g1 < 1) g1 = 1;
    k_partition<<<g1, P_NT, smem1>>>(p);
    int g2 = p.nbins < nsm ? p.nbins : nsm;
    k_gather<<<g2, K2_NT, smem2>>>(p);
}
```

```cpp
#include <cuda_runtime.h>
#include <cuda_bf16.h>
#include <stdint.h>
#include <limits.h>

namespace {

constexpr int DE = 16;
constexpr int NR = 8;
constexpr int NL = 3;

constexpr int NB_LOG = 8;
constexpr int NB = 1 << NB_LOG;
constexpr int MAX_E = 400000;
constexpr int MAX_BINS = (MAX_E + NB - 1) / NB;
constexpr int BINS_PAD = 2048;
constexpr int CAPG = 5120;

constexpr int P_NT = 1024;
constexpr int P_PER = 16;
constexpr int P_TILE_MAX = P_NT * P_PER;
constexpr int P_STAGE = P_TILE_MAX + 3 * MAX_BINS + 16;

constexpr int G_NT = 256;
constexpr int G_BLOCKS = 3;
constexpr int G_PER = CAPG / G_NT;
constexpr int NGRP = NB / 8;
constexpr int CAPS = 5120;
constexpr int G_STAGES = 2;

__device__ uint2 g_records[(size_t)MAX_BINS * CAPG];
__device__ int g_cursor[BINS_PAD];
__device__ uint4 g_frag[4 * 32];
__device__ float g_ovf[(size_t)MAX_BINS * NB * DE];

__device__ __forceinline__ float bf16r(float x) { return __bfloat162float(__float2bfloat16_rn(x)); }
__device__ __forceinline__ float bf16lo(uint32_t v) { return __uint_as_float(v << 16); }
__device__ __forceinline__ float bf16hi(uint32_t v) { return __uint_as_float(v & 0xffff0000u); }
__device__ __forceinline__ float ldbf(const __nv_bfloat16* p) { return __bfloat162float(*p); }
__device__ __forceinline__ uint32_t smem_u32(const void* p) { return (uint32_t)__cvta_generic_to_shared(p); }

__device__ __forceinline__ uint32_t pack_bf16(float lo, float hi) {
    __nv_bfloat162 v = __floats2bfloat162_rn(lo, hi);
    return *reinterpret_cast<uint32_t*>(&v);
}
__device__ __forceinline__ uint32_t mul_bf16x2(uint32_t a, uint32_t b) {
    __nv_bfloat162 r = __hmul2(*reinterpret_cast<__nv_bfloat162*>(&a), *reinterpret_cast<__nv_bfloat162*>(&b));
    return *reinterpret_cast<uint32_t*>(&r);
}
__device__ __forceinline__ uint32_t sub_bf16x2(uint32_t a, uint32_t b) {
    __nv_bfloat162 r = __hsub2(*reinterpret_cast<__nv_bfloat162*>(&a), *reinterpret_cast<__nv_bfloat162*>(&b));
    return *reinterpret_cast<uint32_t*>(&r);
}
__device__ __forceinline__ uint32_t cos_fast_bf16x2(uint32_t x) {
    return pack_bf16(__cosf(bf16lo(x)), __cosf(bf16hi(x)));
}
__constant__ double c_pow2mod2pi[121] = {
    1.0, 2.0, 4.0, 1.7168146928204135,
    3.433629385640827, 0.5840734641020676, 1.1681469282041352, 2.3362938564082705,
    4.672587712816541, 3.0619901184534952, 6.1239802369069904, 5.964775166634395,
    5.646365026089203, 5.009544744998821, 3.7359041828180546, 1.188623058456523,
    2.377246116913046, 4.754492233826092, 3.2257991604725964, 0.1684130137656059,
    0.3368260275312118, 0.6736520550624236, 1.3473041101248473, 2.6946082202496946,
    5.389216440499389, 4.495247573819193, 2.707309840458799, 5.414619680917598,
    4.546054054655609, 2.8089228021316304, 5.617845604263261, 4.952505901346936,
    3.621826495514285, 0.960467683848984, 1.920935367697968, 3.841870735395936,
    1.400556163612285, 2.80111232722457, 5.60222465444914, 4.921264001718693,
    3.5593426962577985, 0.8355000853360102, 1.6710001706720203, 3.3420003413440407,
    0.4008153755084947, 0.8016307510169894, 1.6032615020339789, 3.2065230040679578,
    0.12986070095632937, 0.25972140191265874, 0.5194428038253175, 1.038885607650635,
    2.07777121530127, 4.15554243060254, 2.0278995540254936, 4.055799108050987,
    1.8284129089223877, 3.6568258178447755, 1.030466328509965, 2.06093265701993,
    4.12186531403986, 1.9605453209001322, 3.9210906418002645, 1.5589959764209427,
    3.1179919528418854, 6.235983905683771, 6.188782504187955, 6.094379701196324,
    5.905574095213061, 5.527962883246536, 4.772740459313485, 3.262295611447383,
    0.24140591571517903, 0.48281183143035805, 0.9656236628607161, 1.9312473257214322,
    3.8624946514428644, 1.4418039957061426, 2.883607991412285, 5.76721598282457,
    5.251246658469554, 4.219308009759521, 2.1554307123394554, 4.310861424678911,
    2.338537542178235, 4.67707508435647, 3.0709648615333527, 6.141929723066705,
    6.000674138953824, 5.718162970728061, 5.153140634276536, 4.0230959613734845,
    1.7630066155673831, 3.5260132311347663, 0.7688411550899459, 1.5376823101798918,
    3.0753646203597835, 6.150729240719567, 6.018273174259547, 5.753361041339508,
    5.223536775499429, 4.1638882438192715, 2.0445911804589567, 4.089182360917913,
    1.895179414656241, 3.790358829312482, 1.297532351445378, 2.595064702890756,
    5.190129405781512, 4.097073504383439, 1.9109617015872908, 3.8219234031745817,
    1.360661499169577, 2.721322998339154, 5.442645996678308, 4.602106686177028,
    2.9210280651744704, 5.842056130348941, 5.4009269535182955, 4.518668599857005,
    2.754151892534424,
};
__device__ __forceinline__ float cos_any_bf16(uint32_t u) {
    const uint32_t ef = (u >> 7) & 0xffu;
    float x = __uint_as_float(u << 16);
    if (ef >= 134u) {
        if (ef == 255u) return __uint_as_float(0x7fc00000u);
        const double r = (double)((u & 0x7fu) | 0x80u) * c_pow2mod2pi[ef - 134u];
        x = (float)(r - 6.283185307179586476925 * rint(r * 0.159154943091895335769));
    }
    return __cosf(x);
}
__device__ __forceinline__ uint32_t cos_slow_bf16x2(uint32_t x) {
    return pack_bf16(cos_any_bf16(x & 0xffffu), cos_any_bf16(x >> 16));
}
__device__ __forceinline__ uint32_t rbf_bf16x2(uint32_t dd, uint32_t cc) {
    uint32_t t = sub_bf16x2(dd, cc);
    t = mul_bf16x2(t, t);
    t = mul_bf16x2(t, 0xC120C120u);
    return pack_bf16(__expf(bf16lo(t)), __expf(bf16hi(t)));
}

__device__ __forceinline__ void mma16816(float* d, const uint32_t* a, uint32_t b0, uint32_t b1) {
    asm volatile("mma.sync.aligned.m16n8k16.row.col.f32.bf16.bf16.f32 {%0,%1,%2,%3}, {%4,%5,%6,%7}, {%8,%9}, {%0,%1,%2,%3};"
                 : "+f"(d[0]), "+f"(d[1]), "+f"(d[2]), "+f"(d[3])
                 : "r"(a[0]), "r"(a[1]), "r"(a[2]), "r"(a[3]), "r"(b0), "r"(b1));
}
__device__ __forceinline__ void mma1688(float* d, const uint32_t* a, uint32_t b) {
    asm volatile("mma.sync.aligned.m16n8k8.row.col.f32.bf16.bf16.f32 {%0,%1,%2,%3}, {%4,%5}, {%6}, {%0,%1,%2,%3};"
                 : "+f"(d[0]), "+f"(d[1]), "+f"(d[2]), "+f"(d[3])
                 : "r"(a[0]), "r"(a[1]), "r"(b));
}
__device__ __forceinline__ uint32_t movm(uint32_t a) {
    uint32_t d;
    asm volatile("movmatrix.sync.aligned.m8n8.trans.b16 %0, %1;" : "=r"(d) : "r"(a));
    return d;
}
__device__ __forceinline__ void ldsm_x4_trans(uint32_t* r, uint32_t addr) {
    asm volatile("ldmatrix.sync.aligned.m8n8.x4.trans.shared.b16 {%0,%1,%2,%3}, [%4];"
                 : "=r"(r[0]), "=r"(r[1]), "=r"(r[2]), "=r"(r[3]) : "r"(addr) : "memory");
}
__device__ __forceinline__ void cp_async_row(uint32_t dst, const unsigned char* base, uint32_t w) {
    uint64_t addr;
    asm("mad.wide.u32 %0, %1, 1, %2;" : "=l"(addr) : "r"(w & 0xffffffu), "l"(base));
    asm volatile("{ .reg .pred p; setp.gt.u32 p, %2, 0xffffff; @p cp.async.cg.shared.global [%0], [%1], 16; }" :: "r"(dst), "l"(addr), "r"(w) : "memory");
}
__device__ __forceinline__ void cp_async_commit() { asm volatile("cp.async.commit_group;" ::: "memory"); }
template <int N> __device__ __forceinline__ void cp_async_wait() { asm volatile("cp.async.wait_group %0;" :: "n"(N) : "memory"); }

struct Params {
    const __nv_bfloat16* m;
    const int* idx_in;
    const int* idx_out;
    const __nv_bfloat16* dist;
    const __nv_bfloat16* angle;
    const __nv_bfloat16* centers;
    const __nv_bfloat16* ang_freq;
    const __nv_bfloat16* w_rbf;
    const __nv_bfloat16* w_sbf;
    const __nv_bfloat16* w_down;
    const __nv_bfloat16* w_up;
    __nv_bfloat16* out;
    int E, T, nbins, ntiles, tile;
};

__device__ __forceinline__ float rbf_ref(float d, float c) {
    float u = bf16r(d - c);
    u = bf16r(u * u);
    u = bf16r(-10.0f * u);
    return bf16r(__expf(u));
}
__device__ __noinline__ void slow_bin(const Params* pp, int bin, int tid, int nthr, int barid) {
    const Params& p = *pp;
    for (int t = tid; t < p.T; t += nthr) {
        const int out = p.idx_out[t];
        if ((out >> NB_LOG) != bin) continue;
        const int in = p.idx_in[t];
        const float ang = ldbf(p.angle + t);
        float mrow[DE], rb[NR], cb[NL];
        for (int k = 0; k < DE; k++) mrow[k] = ldbf(p.m + (size_t)in * DE + k);
        float d = ldbf(p.dist + out);
        for (int r = 0; r < NR; r++) rb[r] = rbf_ref(d, ldbf(p.centers + r));
        for (int l = 0; l < NL; l++) cb[l] = bf16r(cosf(bf16r(ldbf(p.ang_freq + l) * ang)));
        for (int c = 0; c < DE; c++) {
            float md = 0.f, s = 0.f;
            for (int k = 0; k < DE; k++) md = fmaf(mrow[k], ldbf(p.w_down + k * DE + c), md);
            for (int r = 0; r < NR; r++)
                for (int l = 0; l < NL; l++) s = fmaf(rb[r] * cb[l], ldbf(p.w_sbf + (r * NL + l) * DE + c), s);
            atomicAdd(&g_ovf[(size_t)out * DE + c], md * s);
        }
    }
    __threadfence();
    asm volatile("bar.sync %0, %1;" :: "r"(barid), "r"(nthr) : "memory");
    for (int i = tid; i < NB * DE; i += nthr) {
        const int e = bin * NB + i / DE, c = i % DE;
        if (e >= p.E) continue;
        float up = 0.f, gate = 0.f;
        for (int k = 0; k < DE; k++) up = fmaf(__ldcg(&g_ovf[(size_t)e * DE + k]), ldbf(p.w_up + k * DE + c), up);
        const float d = ldbf(p.dist + e);
        for (int r = 0; r < NR; r++) gate = fmaf(rbf_ref(d, ldbf(p.centers + r)), ldbf(p.w_rbf + r * DE + c), gate);
        p.out[(size_t)e * DE + c] = __float2bfloat16_rn(fmaf(up, gate, ldbf(p.m + (size_t)e * DE + c)));
    }
    asm volatile("bar.sync %0, %1;" :: "r"(barid), "r"(nthr) : "memory");
    for (int i = tid; i < NB * DE; i += nthr) g_ovf[(size_t)bin * NB * DE + i] = 0.f;
}

__device__ __forceinline__ int4 ld4_guard(const int* p, int i, int n, int fill) {
    if (i + 3 < n) return __ldcs(reinterpret_cast<const int4*>(p + i));
    int4 r;
    r.x = (i + 0 < n) ? p[i + 0] : fill;
    r.y = (i + 1 < n) ? p[i + 1] : fill;
    r.z = (i + 2 < n) ? p[i + 2] : fill;
    r.w = fill;
    return r;
}
__device__ __forceinline__ uint2 ld4h_guard(const unsigned short* p, int i, int n) {
    if (i + 3 < n) return __ldcs(reinterpret_cast<const uint2*>(p + i));
    uint32_t a = (i + 0 < n) ? p[i + 0] : 0u, b = (i + 1 < n) ? p[i + 1] : 0u, c = (i + 2 < n) ? p[i + 2] : 0u;
    return make_uint2(a | (b << 16), c);
}

__global__ void __launch_bounds__(P_NT, 1) k_partition(const __grid_constant__ Params p) {
    extern __shared__ __align__(128) unsigned char smem_raw[];
    uint2* stage = reinterpret_cast<uint2*>(smem_raw);
    int* hist = reinterpret_cast<int*>(smem_raw + (size_t)P_STAGE * 8);
    int* sdelta = hist + BINS_PAD + 4;
    __shared__ int s_total;
    __shared__ int warp_sums[P_NT / 32];
    static_assert(BINS_PAD == 2 * P_NT, "two bins per thread in the scan");

    const int tid = threadIdx.x;
    const int lane = tid & 31, wid = tid >> 5;
    const unsigned short* ang16 = reinterpret_cast<const unsigned short*>(p.angle);
    asm volatile("griddepcontrol.launch_dependents;" ::: "memory");

    if (blockIdx.x == 0 && wid == P_NT / 32 - 1) {
        const int g = lane >> 2, q = lane & 3;
        const unsigned short* wd = reinterpret_cast<const unsigned short*>(p.w_down);
        const unsigned short* wu = reinterpret_cast<const unsigned short*>(p.w_up);
        const unsigned short* ws = reinterpret_cast<const unsigned short*>(p.w_sbf);
        const unsigned short* wr = reinterpret_cast<const unsigned short*>(p.w_rbf);
        uint4 t;
        t.x = (uint32_t)wd[(2 * q) * DE + g] | ((uint32_t)wd[(2 * q + 1) * DE + g] << 16);
        t.y = (uint32_t)wd[(2 * q) * DE + g + 8] | ((uint32_t)wd[(2 * q + 1) * DE + g + 8] << 16);
        t.z = (uint32_t)wd[(2 * q + 8) * DE + g] | ((uint32_t)wd[(2 * q + 9) * DE + g] << 16);
        t.w = (uint32_t)wd[(2 * q + 8) * DE + g + 8] | ((uint32_t)wd[(2 * q + 9) * DE + g + 8] << 16);
        g_frag[lane] = t;
        const int cA = 2 * g, cB = 2 * g + 1;
        t.x = (uint32_t)wu[(2 * q) * DE + cA] | ((uint32_t)wu[(2 * q + 1) * DE + cA] << 16);
        t.y = (uint32_t)wu[(2 * q) * DE + cB] | ((uint32_t)wu[(2 * q + 1) * DE + cB] << 16);
        t.z = (uint32_t)wu[(2 * q + 8) * DE + cA] | ((uint32_t)wu[(2 * q + 9) * DE + cA] << 16);
        t.w = (uint32_t)wu[(2 * q + 8) * DE + cB] | ((uint32_t)wu[(2 * q + 9) * DE + cB] << 16);
        g_frag[32 + lane] = t;
        uint32_t sb[NL][2];
#pragma unroll
        for (int l = 0; l < NL; l++) {
            sb[l][0] = (uint32_t)ws[((2 * q) * NL + l) * DE + g] | ((uint32_t)ws[((2 * q + 1) * NL + l) * DE + g] << 16);
            sb[l][1] = (uint32_t)ws[((2 * q) * NL + l) * DE + g + 8] | ((uint32_t)ws[((2 * q + 1) * NL + l) * DE + g + 8] << 16);
        }
        g_frag[64 + lane] = make_uint4(sb[0][0], sb[0][1], sb[1][0], sb[1][1]);
        t.x = sb[2][0]; t.y = sb[2][1];
        t.z = (uint32_t)wr[(2 * q) * DE + cA] | ((uint32_t)wr[(2 * q + 1) * DE + cA] << 16);
        t.w = (uint32_t)wr[(2 * q) * DE + cB] | ((uint32_t)wr[(2 * q + 1) * DE + cB] << 16);
        g_frag[96 + lane] = t;
    }

    int4 O[P_PER / 4], I[P_PER / 4];
    uint2 A[P_PER / 4];
    int tile = blockIdx.x;
    if (tile < p.ntiles) {
        const int base = tile * p.tile, n = min(p.tile, p.T - base);
#pragma unroll
        for (int v = 0; v < P_PER / 4; v++) O[v] = ld4_guard(p.idx_out + base, (v * P_NT + tid) * 4, n, -1);
#pragma unroll
        for (int v = 0; v < P_PER / 4; v++) {
            I[v] = ld4_guard(p.idx_in + base, (v * P_NT + tid) * 4, n, 0);
            A[v] = ld4h_guard(ang16 + base, (v * P_NT + tid) * 4, n);
        }
    }
    reinterpret_cast<int2*>(hist)[tid] = make_int2(0, 0);
    if (tid == 0) hist[BINS_PAD] = 0;
    for (; tile < p.ntiles; tile += gridDim.x) {
        const int base = tile * p.tile, n = min(p.tile, p.T - base);
        __syncthreads();
#pragma unroll
        for (int v = 0; v < P_PER / 4; v++) {
            atomicAdd(&hist[min((uint32_t)O[v].x >> NB_LOG, (uint32_t)BINS_PAD)], 1);
            atomicAdd(&hist[min((uint32_t)O[v].y >> NB_LOG, (uint32_t)BINS_PAD)], 1);
            atomicAdd(&hist[min((uint32_t)O[v].z >> NB_LOG, (uint32_t)BINS_PAD)], 1);
            atomicAdd(&hist[min((uint32_t)O[v].w >> NB_LOG, (uint32_t)BINS_PAD)], 1);
        }
        __syncthreads();
        const int2 c2 = reinterpret_cast<int2*>(hist)[tid];
        const int pc0 = (c2.x + 3) & ~3, pc1 = (c2.y + 3) & ~3;
        int g0 = 0, g1 = 0;
        if (pc0) g0 = atomicAdd(&g_cursor[2 * tid], pc0);
        if (pc1) g1 = atomicAdd(&g_cursor[2 * tid + 1], pc1);
        const int s = pc0 + pc1;
        int inc = s;
#pragma unroll
        for (int o = 1; o < 32; o <<= 1) {
            int t = __shfl_up_sync(0xffffffffu, inc, o);
            if (lane >= o) inc += t;
        }
        if (lane == 31) warp_sums[wid] = inc;
        __syncthreads();
        int woff;
        {
            int ws = warp_sums[lane];
            int winc = ws;
#pragma unroll
            for (int o = 1; o < 32; o <<= 1) {
                int t = __shfl_up_sync(0xffffffffu, winc, o);
                if (lane >= o) winc += t;
            }
            woff = __shfl_sync(0xffffffffu, winc - ws, wid);
        }
        const int e0 = woff + inc - s, e1 = e0 + pc0;
        reinterpret_cast<int2*>(hist)[tid] = make_int2(e0, e1);
        if (tid == 0) hist[BINS_PAD] = P_STAGE;
        for (int k = c2.x; k < pc0; k++) stage[e0 + k] = make_uint2(0u, 0xffffffffu);
        for (int k = c2.y; k < pc1; k++) stage[e1 + k] = make_uint2(0u, 0xffffffffu);
        __syncthreads();
#pragma unroll
        for (int v = 0; v < P_PER / 4; v++) {
            const uint32_t o[4] = {(uint32_t)O[v].x, (uint32_t)O[v].y, (uint32_t)O[v].z, (uint32_t)O[v].w};
            const uint32_t in[4] = {(uint32_t)I[v].x, (uint32_t)I[v].y, (uint32_t)I[v].z, (uint32_t)I[v].w};
            const uint32_t an[4] = {A[v].x & 0xffffu, A[v].x >> 16, A[v].y & 0xffffu, A[v].y >> 16};
#pragma unroll
            for (int u = 0; u < 4; u++) {
                int pos = atomicAdd(&hist[min(o[u] >> NB_LOG, (uint32_t)BINS_PAD)], 1);
                stage[min(pos, P_STAGE - 1)] = make_uint2((in[u] << 5) | (0x1000000u << (o[u] & 7)), an[u] | ((o[u] & 255u) << 16));
            }
        }
        {
            const int nt = tile + gridDim.x;
            if (nt < p.ntiles) {
                const int nbase = nt * p.tile, nn = min(p.tile, p.T - nbase);
#pragma unroll
                for (int v = 0; v < P_PER / 4; v++) O[v] = ld4_guard(p.idx_out + nbase, (v * P_NT + tid) * 4, nn, -1);
#pragma unroll
                for (int v = 0; v < P_PER / 4; v++) {
                    I[v] = ld4_guard(p.idx_in + nbase, (v * P_NT + tid) * 4, nn, 0);
                    A[v] = ld4h_guard(ang16 + nbase, (v * P_NT + tid) * 4, nn);
                }
            }
        }
        {
            const int d0 = (g0 + pc0 <= CAPG) ? (2 * tid) * CAPG + g0 - e0 : INT_MIN;
            const int d1 = (g1 + pc1 <= CAPG) ? (2 * tid + 1) * CAPG + g1 - e1 : INT_MIN;
            for (int k = e0 >> 2; k < (e1 >> 2); k++) sdelta[k] = d0;
            for (int k = e1 >> 2; k < ((e1 + pc1) >> 2); k++) sdelta[k] = d1;
            if (tid == P_NT - 1) s_total = e1 + pc1;
        }
        __syncthreads();
        {
            const int nch = s_total >> 1;
#pragma unroll 4
            for (int i = tid; i < nch; i += P_NT) {
                const uint4 v = reinterpret_cast<const uint4*>(stage)[i];
                const int d = sdelta[i >> 1];
                if (d != INT_MIN) *reinterpret_cast<uint4*>(g_records + (size_t)(uint32_t)(2 * i + d)) = v;
            }
        }
        reinterpret_cast<int2*>(hist)[tid] = make_int2(0, 0);
        if (tid == 0) hist[BINS_PAD] = 0;
    }
}

constexpr int SM_IDX = 0;
constexpr int SM_ANG = SM_IDX + (CAPS + 32) * 4;
constexpr int SM_STG = SM_ANG + (CAPS + 64) * 2;
constexpr int SM_RING = SM_STG + (G_NT / 32 + 1) * 512;
constexpr int SM_TOTAL = SM_RING + (G_NT / 32) * G_STAGES * 1024;

__device__ __forceinline__ uint2 lds64(uint32_t a) { uint2 v; asm volatile("ld.shared.v2.u32 {%0,%1}, [%2];" : "=r"(v.x), "=r"(v.y) : "r"(a) : "memory"); return v; }

__device__ __forceinline__ uint32_t lds16(uint32_t a) { uint16_t v; asm volatile("ld.shared.u16 %0, [%1];" : "=h"(v) : "r"(a) : "memory"); return v; }
__device__ __forceinline__ void sts16(uint32_t a, uint32_t v) { asm volatile("st.shared.u16 [%0], %1;" :: "r"(a), "h"((uint16_t)v) : "memory"); }
__device__ __forceinline__ void make_cbf(uint32_t ang, uint32_t f01, uint32_t f2m, uint32_t a01, uint32_t a2) {
    const uint32_t aa = ang * 0x10001u;
    const uint32_t x01 = mul_bf16x2(aa, f01);
    const uint32_t x2m = mul_bf16x2(aa, f2m);
    uint32_t c01, c2;
    if ((x2m & 0x7fff0000u) < 0x43000000u) {
        c01 = cos_fast_bf16x2(x01);
        c2 = pack_bf16(__cosf(bf16lo(x2m)), 0.f);
    } else {
        c01 = cos_slow_bf16x2(x01);
        c2 = pack_bf16(cos_any_bf16(x2m & 0xffffu), 0.f);
    }
    sts16(a01, c01);
    sts16(a01 + 8, c01 >> 16);
    sts16(a2, c2);
}

__global__ void __launch_bounds__(G_NT, G_BLOCKS) k_gather(const __grid_constant__ Params p) {
    extern __shared__ __align__(128) unsigned char smem_raw[];
    uint32_t* sidx = reinterpret_cast<uint32_t*>(smem_raw + SM_IDX);
    unsigned short* sang = reinterpret_cast<unsigned short*>(smem_raw + SM_ANG);
    __shared__ int cnts[NB + 32];
    __shared__ int gstart[NGRP + 1];
    __shared__ int warp_sums[NB / 32];

    const int tid = threadIdx.x;
    const int lane = tid & 31, wid = tid >> 5;
    const int bin = blockIdx.x;
    asm volatile("griddepcontrol.wait;" ::: "memory");
    const int total = g_cursor[bin];
    bool ovf = total > CAPG;
    const int n = ovf ? 0 : total;

    const uint4* rec = reinterpret_cast<const uint4*>(g_records + (size_t)bin * CAPG) + tid;
    uint4 r[G_PER / 2];
#pragma unroll
    for (int j = 0; j < G_PER / 2; j++) {
        r[j] = make_uint4(0u, 0xffffffffu, 0u, 0xffffffffu);
        if ((j * G_NT + tid) * 2 < n) r[j] = __ldcs(rec + j * G_NT);
    }
    if (tid < NB) cnts[tid] = 0;
#pragma unroll
    for (int i = 0; i < G_STAGES * 2; i++)
        reinterpret_cast<uint4*>(smem_raw + SM_RING)[i * G_NT + tid] = make_uint4(0u, 0u, 0u, 0u);
    const unsigned short* fq = reinterpret_cast<const unsigned short*>(p.ang_freq);
    const uint32_t f01 = (uint32_t)fq[0] | ((uint32_t)fq[1] << 16);
    const uint32_t f2m = (uint32_t)fq[2] | (max(max((uint32_t)fq[0] & 0x7fffu, (uint32_t)fq[1] & 0x7fffu), (uint32_t)fq[2] & 0x7fffu) << 16);
    const uint32_t dkey = NB + lane;
    __syncthreads();
    if (tid == 0) g_cursor[bin] = 0;
#pragma unroll
    for (int j = 0; j < G_PER / 2; j++) {
        atomicAdd(&cnts[min(r[j].y >> 16, dkey)], 1);
        atomicAdd(&cnts[min(r[j].w >> 16, dkey)], 1);
    }
    __syncthreads();
    int c = 0, inc = 0, cp = 0, npad = 0, est = 0;
    if (tid < NB) {
        c = cnts[tid];
        int gt = c;
        gt += __shfl_xor_sync(0xffffffffu, gt, 1);
        gt += __shfl_xor_sync(0xffffffffu, gt, 2);
        gt += __shfl_xor_sync(0xffffffffu, gt, 4);
        npad = ((gt + 31) & ~31) - gt;
        cp = c + (((lane & 7) == 7) ? npad : 0);
        inc = cp;
#pragma unroll
        for (int o = 1; o < 32; o <<= 1) {
            int t = __shfl_up_sync(0xffffffffu, inc, o);
            if (lane >= o) inc += t;
        }
        if (lane == 31) warp_sums[wid] = inc;
    }
    __syncthreads();
    {
        int woff = 0, tot = 0;
#pragma unroll
        for (int w = 0; w < NB / 32; w++) { woff += (w < wid) ? warp_sums[w] : 0; tot += warp_sums[w]; }
        ovf = ovf || (tot > CAPS);
        if (tid < NB) {
            const int st = ovf ? 0 : woff + inc - cp;
            est = st;
            cnts[tid] = ovf ? CAPS : st;
            if ((lane & 7) == 0) gstart[tid >> 3] = st;
            if (tid == NB - 1) gstart[NGRP] = ovf ? 0 : tot;
            if (tid < 32) cnts[NB + tid] = CAPS;
            const int gend = __shfl_sync(0xffffffffu, woff + inc, lane | 7);
            if (!ovf) {
#pragma unroll
                for (int k = 0; k < 4; k++) {
                    const int kk = (lane & 7) + 8 * k;
                    if (kk < npad) { sidx[gend - 1 - kk] = 0u; sang[gend - 1 - kk] = 0; }
                }
            }
        }
    }
    __syncthreads();
#pragma unroll
    for (int j = 0; j < G_PER / 2; j++) {
        {
            const int pos = min(atomicAdd(&cnts[min(r[j].y >> 16, dkey)], 1), CAPS);
            sidx[pos] = r[j].x;
            sang[pos] = (unsigned short)r[j].y;
        }
        {
            const int pos = min(atomicAdd(&cnts[min(r[j].w >> 16, dkey)], 1), CAPS);
            sidx[pos] = r[j].z;
            sang[pos] = (unsigned short)r[j].w;
        }
    }
    __syncthreads();

    if (ovf) {
        slow_bin(&p, bin, tid, G_NT, 0);
        return;
    }
    const int g = lane >> 2, q = lane & 3;
    constexpr int GPW = NGRP / (G_NT / 32);
    const int grp0 = wid * GPW;
    const int wbeg = gstart[grp0], wend = gstart[grp0 + GPW];
    const unsigned char* mb = reinterpret_cast<const unsigned char*>(p.m);
    const uint32_t sbase = smem_u32(smem_raw);

    const uint32_t ring = sbase + SM_RING + wid * (G_STAGES * 1024);
    const int cj = lane >> 1;
    const int crow = (cj >> 2) * 2 + (cj & 1) + ((cj >> 1) & 1) * 8;
    const uint32_t cdst = ring + (uint32_t)(crow * 32 + (((lane ^ (crow >> 2)) & 1) * 16));
    const unsigned char* msrc = mb + (lane & 1) * 16;
    const int lrow = (lane >> 4) * 8 + (lane & 7);
    const uint32_t lsrc = ring + (uint32_t)(lrow * 32 + ((((lane >> 3) ^ (lrow >> 2)) & 1) * 16));

    uint32_t iaddr = sbase + SM_IDX + (wbeg + 2 * cj) * 4;
    const uint32_t iend = sbase + SM_IDX + wend * 4;
    uint32_t ioff = 0;
#pragma unroll
    for (int k = 0; k < G_STAGES - 1; k++) {
        if (iaddr < iend) {
            const uint2 w = lds64(iaddr);
            cp_async_row(cdst + ioff, msrc, w.x);
            cp_async_row(cdst + ioff + 512, msrc, w.y);
        }
        cp_async_commit();
        iaddr += 128; ioff += 1024;
    }

    const uint32_t cen = reinterpret_cast<const uint32_t*>(p.centers)[q];

    const int ew = bin * NB + grp0 * 8;
    const unsigned short* pdist = reinterpret_cast<const unsigned short*>(p.dist) + ew + g;
    const uint32_t moff0 = (uint32_t)(ew + 2 * q) * 32u + 4u * g;
    const int nleft = p.E - ew;
    uint32_t dgn = (g < nleft) ? (uint32_t)pdist[0] : 0u;
    uint32_t man = (2 * q < nleft) ? __ldg(reinterpret_cast<const uint32_t*>(mb + moff0)) : 0u;
    uint32_t mbn = (2 * q + 1 < nleft) ? __ldg(reinterpret_cast<const uint32_t*>(mb + moff0 + 32)) : 0u;

    uint2 wnext = make_uint2(0u, 0u);
    if (iaddr < iend) wnext = lds64(iaddr);
    const uint32_t stg = ((sbase + SM_STG + 511u) & ~511u) + wid * 512;
    uint32_t sw01 = stg + (uint32_t)((lane & 1) * 64 + (lane >> 3) * 16 + ((lane & 7) >> 1) * 2);
    uint32_t sw2 = stg + (uint32_t)(128 + (lane >> 3) * 16 + (lane & 1) * 8 + ((lane & 7) >> 1) * 2);
    uint32_t ac = stg + q * 16;
    uint32_t aaddr = sbase + SM_ANG + (wbeg + lane) * 2;
    const uint32_t aend = sbase + SM_ANG + wend * 2;
    make_cbf((aaddr < aend) ? lds16(aaddr) : 0u, f01, f2m, sw01, sw2);
    aaddr += 64;
    uint32_t anext = (aaddr < aend) ? lds16(aaddr) : 0u;
    __syncwarp();
    int rel = wbeg + 8 * q;
    static_assert(NB == G_NT, "edge ownership");
    uint4 cA = make_uint4(0u, 0u, 0u, 0u), cB = cA, c2 = cA;
#pragma unroll 1
    for (int gi = 0; gi < GPW; gi++) {
        const int gend = gstart[grp0 + gi + 1];
        const int es = __shfl_sync(0xffffffffu, est, gi * 8 + g);
        const int ee = es + __shfl_sync(0xffffffffu, c, gi * 8 + g);
        const uint32_t moff = moff0 + gi * 256;
        const bool va = gi * 8 + 2 * q < nleft, vb = gi * 8 + 2 * q + 1 < nleft;
        const uint32_t dg = dgn, ma = man, mbv = mbn;
        if (gi + 1 < GPW) {
            dgn = (gi * 8 + 8 + g < nleft) ? (uint32_t)pdist[gi * 8 + 8] : 0u;
            man = (gi * 8 + 8 + 2 * q < nleft) ? __ldg(reinterpret_cast<const uint32_t*>(mb + moff + 256)) : 0u;
            mbn = (gi * 8 + 9 + 2 * q < nleft) ? __ldg(reinterpret_cast<const uint32_t*>(mb + moff + 288)) : 0u;
        }

        float D[NL][4];
#pragma unroll
        for (int l = 0; l < NL; l++)
#pragma unroll
            for (int c4 = 0; c4 < 4; c4++) D[l][c4] = 0.f;
#pragma unroll 1
        while (rel < gend) {
            cp_async_row(cdst + ioff, msrc, wnext.x);
            cp_async_row(cdst + ioff + 512, msrc, wnext.y);
            cp_async_commit();
            iaddr += 128; ioff = (ioff == (G_STAGES - 1) * 1024) ? 0 : ioff + 1024;
            wnext = make_uint2(0u, 0u);
            if (iaddr < iend) wnext = lds64(iaddr);
            uint32_t mlo, mhi;
            asm("shl.b32 %0, %1, %2;" : "=r"(mlo) : "r"(0xffu), "r"((uint32_t)max(es - rel, 0)));
            asm("shl.b32 %0, %1, %2;" : "=r"(mhi) : "r"(0xffffffffu), "r"((uint32_t)max(ee - rel, 0)));
            const uint32_t bits = mlo & ~mhi & 0xffu;
            asm volatile("{ .reg .pred pa, pb, pc; setp.ne.u32 pa, %13, 0; setp.ne.u32 pb, %14, 0; or.pred pc, pa, pb;\n\t"
                         "@pa ld.shared.v4.u32 {%0,%1,%2,%3}, [%12];\n\t"
                         "@pb ld.shared.v4.u32 {%4,%5,%6,%7}, [%12+64];\n\t"
                         "@pc ld.shared.v4.u32 {%8,%9,%10,%11}, [%12+128]; }"
                         : "+r"(cA.x), "+r"(cA.y), "+r"(cA.z), "+r"(cA.w), "+r"(cB.x), "+r"(cB.y), "+r"(cB.z), "+r"(cB.w),
                           "+r"(c2.x), "+r"(c2.y), "+r"(c2.z), "+r"(c2.w)
                         : "r"(ac), "r"(bits & 0x55u), "r"(bits & 0xaau) : "memory");
            rel += 32;
            ac ^= 256u; sw01 ^= 256u; sw2 ^= 256u;
            make_cbf(anext, f01, f2m, sw01, sw2);
            aaddr += 64;
            anext = (aaddr < aend) ? lds16(aaddr) : 0u;
            const uint32_t u = bits * 0x4001u;
            const uint32_t kA0 = (u & 0x10001u) * 0x3F80u, kB0 = (u & 0x20002u) * 0x1FC0u;
            const uint32_t kA1 = (u & 0x100010u) * 0x3F8u, kB1 = (u & 0x200020u) * 0x1FCu;
            cp_async_wait<G_STAGES - 1>();
            __syncwarp();
            uint32_t a[4], b[4];
            ldsm_x4_trans(a, lsrc + ioff);
            ldsm_x4_trans(b, lsrc + ioff + 512);
            mma16816(D[0], a, mul_bf16x2(cA.x, kA0), mul_bf16x2(cA.y, kA1));
            mma16816(D[1], a, mul_bf16x2(cA.z, kA0), mul_bf16x2(cA.w, kA1));
            mma16816(D[2], a, mul_bf16x2(c2.x, kA0), mul_bf16x2(c2.y, kA1));
            mma16816(D[0], b, mul_bf16x2(cB.x, kB0), mul_bf16x2(cB.y, kB1));
            mma16816(D[1], b, mul_bf16x2(cB.z, kB0), mul_bf16x2(cB.w, kB1));
            mma16816(D[2], b, mul_bf16x2(c2.z, kB0), mul_bf16x2(c2.w, kB1));
        }
        uint32_t adown[4], aup[4], asbf[NL][2], arb[2];
        {
            const uint4* fr = reinterpret_cast<const uint4*>(g_frag) + lane;
            uint4 t0, t1, t2, t3;
            asm volatile("ld.global.nc.v4.u32 {%0,%1,%2,%3}, [%4];" : "=r"(t0.x), "=r"(t0.y), "=r"(t0.z), "=r"(t0.w) : "l"(fr));
            asm volatile("ld.global.nc.v4.u32 {%0,%1,%2,%3}, [%4];" : "=r"(t2.x), "=r"(t2.y), "=r"(t2.z), "=r"(t2.w) : "l"(fr + 64));
            asm volatile("ld.global.nc.v4.u32 {%0,%1,%2,%3}, [%4];" : "=r"(t3.x), "=r"(t3.y), "=r"(t3.z), "=r"(t3.w) : "l"(fr + 96));
            asm volatile("ld.global.nc.v4.u32 {%0,%1,%2,%3}, [%4];" : "=r"(t1.x), "=r"(t1.y), "=r"(t1.z), "=r"(t1.w) : "l"(fr + 32));
            adown[0] = t0.x; adown[1] = t0.y; adown[2] = t0.z; adown[3] = t0.w;
            aup[0] = t1.x; aup[1] = t1.y; aup[2] = t1.z; aup[3] = t1.w;
            asbf[0][0] = t2.x; asbf[0][1] = t2.y; asbf[1][0] = t2.z; asbf[1][1] = t2.w;
            asbf[2][0] = t3.x; asbf[2][1] = t3.y; arb[0] = t3.z; arb[1] = t3.w;
        }
        const uint32_t brbf = rbf_bf16x2(dg * 0x10001u, cen);
        float agg[4] = {0.f, 0.f, 0.f, 0.f};
#pragma unroll
        for (int l = 0; l < NL; l++) {
            const uint32_t h0 = movm(pack_bf16(D[l][0], D[l][1]));
            const uint32_t h1 = movm(pack_bf16(D[l][2], D[l][3]));
            float S[4] = {0.f, 0.f, 0.f, 0.f};
            float G[4] = {0.f, 0.f, 0.f, 0.f};
            mma16816(S, adown, h0, h1);
            mma1688(G, asbf[l], brbf);
#pragma unroll
            for (int c4 = 0; c4 < 4; c4++) agg[c4] = fmaf(S[c4], G[c4], agg[c4]);
        }
        {
            const uint32_t h0 = movm(pack_bf16(agg[0], agg[1]));
            const uint32_t h1 = movm(pack_bf16(agg[2], agg[3]));
            float U[4] = {0.f, 0.f, 0.f, 0.f};
            float R[4] = {0.f, 0.f, 0.f, 0.f};
            mma16816(U, aup, h0, h1);
            mma1688(R, arb, brbf);
            uint32_t oa = pack_bf16(fmaf(U[0], R[0], bf16lo(ma)), fmaf(U[2], R[2], bf16hi(ma)));
            uint32_t ob = pack_bf16(fmaf(U[1], R[1], bf16lo(mbv)), fmaf(U[3], R[3], bf16hi(mbv)));
            unsigned char* ob8 = reinterpret_cast<unsigned char*>(p.out);
            if (va) *reinterpret_cast<uint32_t*>(ob8 + moff) = oa;
            if (vb) *reinterpret_cast<uint32_t*>(ob8 + moff + 32) = ob;
        }
    }
}

}

extern "C" void kernel_launch(void* const* d_in, const int* in_sizes, int n_in,
                              void* d_out, int out_size) {
    Params p;
    p.m = (const __nv_bfloat16*)d_in[0];
    p.idx_in = (const int*)d_in[1];
    p.idx_out = (const int*)d_in[2];
    p.dist = (const __nv_bfloat16*)d_in[3];
    p.angle = (const __nv_bfloat16*)d_in[4];
    p.centers = (const __nv_bfloat16*)d_in[5];
    p.ang_freq = (const __nv_bfloat16*)d_in[6];
    p.w_rbf = (const __nv_bfloat16*)d_in[7];
    p.w_sbf = (const __nv_bfloat16*)d_in[8];
    p.w_down = (const __nv_bfloat16*)d_in[9];
    p.w_up = (const __nv_bfloat16*)d_in[10];
    p.out = (__nv_bfloat16*)d_out;
    p.E = in_sizes[3];
    p.T = in_sizes[1];
    p.nbins = (p.E + NB - 1) / NB;

    const int smem1 = P_STAGE * 8 + (BINS_PAD + 4) * 4 + (P_STAGE / 4 + 4) * 4;
    const int smem2 = SM_TOTAL;
    static int nsm = 0;
    if (!nsm) {
        cudaFuncSetAttribute(k_partition, cudaFuncAttributeMaxDynamicSharedMemorySize, smem1);
        cudaFuncSetAttribute(k_gather, cudaFuncAttributeMaxDynamicSharedMemorySize, smem2);
        int dev = 0;
        cudaGetDevice(&dev);
        cudaDeviceGetAttribute(&nsm, cudaDevAttrMultiProcessorCount, dev);
    }
    long long per_sm = ((long long)p.T + nsm - 1) / nsm;
    int k = (int)((per_sm + P_TILE_MAX - 1) / P_TILE_MAX);
    if (k < 1) k = 1;
    long long tile = ((long long)p.T + (long long)k * nsm - 1) / ((long long)k * nsm);
    tile = (tile + 15) & ~15LL;
    if (tile > P_TILE_MAX) tile = P_TILE_MAX;
    if (tile < 16) tile = 16;
    p.tile = (int)tile;
    p.ntiles = (int)(((long long)p.T + tile - 1) / tile);
    int g1 = p.ntiles < nsm ? p.ntiles : nsm;
    if (g1 < 1) g1 = 1;
    k_partition<<<g1, P_NT, smem1, cudaStreamPerThread>>>(p);
    {
        cudaLaunchConfig_t cfg = {};
        cfg.gridDim = dim3(p.nbins); cfg.blockDim = dim3(G_NT); cfg.dynamicSmemBytes = smem2;
        cfg.stream = cudaStreamPerThread;
        cudaLaunchAttribute at[1];
        at[0].id = cudaLaunchAttributeProgrammaticStreamSerialization;
        at[0].val.programmaticStreamSerializationAllowed = 1;
        cfg.attrs = at; cfg.numAttrs = 1;
        cudaLaunchKernelEx(&cfg, k_gather, p);
    }
}
```
